```python
import torch

def _softmax(x, axis=-1):
    return torch.softmax(x, dim=axis)
def _gelu(x):
    return torch.nn.functional.gelu(x, approximate="tanh")
def _silu(x):
    return torch.nn.functional.silu(x)
def _sigmoid(x):
    return torch.sigmoid(x)
def _layernorm(x, axis=-1, eps=1e-5):
    m = x.mean(dim=axis, keepdim=True)
    v = x.var(dim=axis, keepdim=True, unbiased=False)
    return (x - m) / torch.sqrt(v + eps)
def _scatter_add(tgt, idx, src, axis=0):
    return tgt.clone().index_add_(axis, idx, src)
def _segment_sum(src, seg, n):
    out = torch.zeros((n,) + src.shape[1:], dtype=src.dtype)
    return out.index_add_(0, seg, src)
def _pad(x, pw):
    flat = tuple(v for pair in reversed(pw) for v in pair)
    return torch.nn.functional.pad(x, flat)

kernel_name = 'recurrent_scan__gqa_block_cached__glu_gated_reglu__decode'

def setup_inputs():

    _w = (lambda a: (lambda t: t.to(torch.bfloat16) if t.is_floating_point() else t)(torch.as_tensor(a)))
    def _A_setup():
        B, Sq, D = 4, 1, 576
        Hq, Hkv, Sk, Dh = 32, 16, 8192, 128
        assert Hq % Hkv == 0, (Hq, Hkv)
        return {
            "x": _w((lambda *s: torch.randn(*s, dtype=torch.bfloat16) * 0.2)(B, Sq, D)),
            "k_cache": _w((lambda *s: torch.randn(*s, dtype=torch.bfloat16) * 1.6)(B, Hkv, Sk, Dh)),
            "v_cache": _w((lambda *s: torch.randn(*s, dtype=torch.bfloat16) * 1.6)(B, Hkv, Sk, Dh)),
            "wq": _w((lambda *s: torch.randn(*s, dtype=torch.bfloat16) * 1.6)(D, Hq * Dh) * (D ** -0.5)),
            "wo": _w((lambda *s: torch.randn(*s, dtype=torch.bfloat16) * 1.6)(Hq * Dh, D) * ((Hq * Dh) ** -0.5)),
        }
    _A_in = _A_setup()

    def _B_setup():
        B, S, D, F = 4, 1, 576, 4608
        return {
            "x": _w((lambda *s: torch.randn(*s, dtype=torch.bfloat16) * 0.2)(B, S, D)),
            "W_gate": _w((lambda *s: torch.randn(*s, dtype=torch.bfloat16) * 0.8)(D, F) * (2.0 / D) ** 0.5),
            "W_up": _w((lambda *s: torch.randn(*s, dtype=torch.bfloat16) * 0.8)(D, F) * (2.0 / D) ** 0.5),
            "W_down": _w((lambda *s: torch.randn(*s, dtype=torch.bfloat16) * 0.8)(F, D) * (1.0 / F) ** 0.5),
        }
    _B_in = _B_setup()

    return {
        "A_x": _A_in["x"],
        "A_k_cache": _A_in["k_cache"],
        "A_v_cache": _A_in["v_cache"],
        "A_wq": _A_in["wq"],
        "A_wo": _A_in["wo"],
        "B_x": _B_in["x"],
        "B_W_gate": _B_in["W_gate"],
        "B_W_up": _B_in["W_up"],
        "B_W_down": _B_in["W_down"],
    }

def reference(A_x, A_k_cache, A_v_cache, A_wq, A_wo, B_x, B_W_gate, B_W_up, B_W_down):
    def _A_ref(x, k_cache, v_cache, wq, wo):
        B, Sq, D = x.shape
        Hq, Dh = 32, 128
        Hkv = k_cache.shape[1]
        rep = Hq // Hkv
        q = (lambda x, *d: x.permute(*d))((x @ wq).reshape(B, Sq, Hq, Dh), 0, 2, 1, 3)
        k = (lambda x, n, axis: torch.repeat_interleave(x, n, dim=axis))(k_cache, rep, axis=1)
        v = (lambda x, n, axis: torch.repeat_interleave(x, n, dim=axis))(v_cache, rep, axis=1)
        scores = torch.einsum("bhqd,bhkd->bhqk", q, k) * (Dh ** -0.5)
        p = _softmax(scores, axis=-1)
        o = torch.einsum("bhqk,bhkd->bhqd", p, v)
        return (lambda x, *d: x.permute(*d))(o, 0, 2, 1, 3).reshape(B, Sq, Hq * Dh) @ wo

    def _B_ref(x, W_gate, W_up, W_down):
        gate = torch.einsum("bsd,df->bsf", x, W_gate)
        up = torch.einsum("bsd,df->bsf", x, W_up)
        gate = gate * (lambda x, dt: x.to(dt))(gate > 0, gate.dtype)
        h = gate * up
        return torch.einsum("bsf,fd->bsd", h, W_down)

    x = A_x
    xn = _layernorm(x, axis=-1)
    s = _A_ref(xn, A_k_cache, A_v_cache, A_wq, A_wo)
    g = _silu(_B_ref(xn, B_W_gate, B_W_up, B_W_down))
    return x + s * g
```

```cpp
#include <cuda_runtime.h>
#include <cuda_bf16.h>
#include <cuda.h>
#include <stdint.h>

namespace {

constexpr int kB = 4, kD = 576, kHQ = 32, kHKV = 16, kSK = 8192, kDH = 128, kF = 4608;
constexpr int kNPair = kB * kHKV;
constexpr int kUnitKeys = 64;
constexpr int kUnitsPerPair = kSK / kUnitKeys;
constexpr int kNUnits = kNPair * kUnitsPerPair;
constexpr int kNOwner = 128;
constexpr int kNFfn = kF / 32;
constexpr int kNFin = (kB * kD) / 32;
constexpr int kMaxGrid = 144;

constexpr int kNS = 9;
constexpr int kSlotBytes = 16384;
constexpr int kWRow = 1168;
constexpr int kWBytes = 32 * kWRow;
constexpr int kBoxRows = 192;
constexpr int kBoxBytes = kBoxRows * 64;

constexpr int kOffRing = 0;
constexpr int kOffW = kOffRing + kNS * kSlotBytes;
constexpr int kOffQ = kOffW + kWBytes;
constexpr int kOffXn = kOffQ + 32768;
constexpr int kOffS = kOffXn + 4 * kWRow;
constexpr int kOffHA = kOffS + 2 * 2 * 72 * 4;
constexpr int kOffOA = kOffHA + 4 * 80;
constexpr int kOffRed = kOffOA + 4 * 80;
constexpr int kOffBar = kOffRed + 4 * 32 * 4;
constexpr int kNBar = 2 * kNS + 5;
constexpr int kOffMeta = kOffBar + kNBar * 8;
constexpr int kOffMisc = kOffMeta + kNS * 4;
constexpr int kSmemUsed = kOffMisc + 16;
constexpr int kSmemBytes = kSmemUsed + 1024;
static_assert(kOffW % 128 == 0 && kOffQ % 16 == 0 && kOffXn % 16 == 0 && kOffS % 16 == 0, "align");
static_assert(kOffBar % 8 == 0, "align");
static_assert(kSmemBytes <= 232448, "smem");

constexpr int kThreads = 288;
constexpr uint32_t kSpinLimit = 1u << 24;

__device__ float g_part_o[(size_t)kNPair * 2 * 4 * kUnitsPerPair * 32];
__device__ float g_part_ml[(size_t)kNPair * 2 * kUnitsPerPair * 2];
__device__ float g_dslot[(size_t)kNFfn * kB * kD];
__device__ float g_sslot[(size_t)kNOwner * kB * kD];
__device__ uint32_t g_q[kNPair * 2 * 4 * 16];
__device__ unsigned long long g_qcount;
__device__ unsigned int g_ticket;

__device__ __forceinline__ uint32_t smem_u32(const void* p) { return (uint32_t)__cvta_generic_to_shared(p); }
__device__ __forceinline__ void mbar_init(uint32_t a, uint32_t c) {
    asm volatile("mbarrier.init.shared::cta.b64 [%0], %1;" ::"r"(a), "r"(c) : "memory");
}
__device__ __forceinline__ void mbar_expect_tx(uint32_t a, uint32_t bytes) {
    asm volatile("mbarrier.arrive.expect_tx.shared::cta.b64 _, [%0], %1;" ::"r"(a), "r"(bytes) : "memory");
}
__device__ __forceinline__ void mbar_arrive(uint32_t a) {
    asm volatile("mbarrier.arrive.shared::cta.b64 _, [%0];" ::"r"(a) : "memory");
}
__device__ __forceinline__ bool mbar_try(uint32_t a, uint32_t parity) {
    uint32_t ok;
    asm volatile(
        "{\n.reg .pred p;\n"
        "mbarrier.try_wait.parity.shared::cta.b64 p, [%1], %2;\n"
        "selp.u32 %0, 1, 0, p;\n}"
        : "=r"(ok) : "r"(a), "r"(parity) : "memory");
    return ok != 0;
}
__device__ __forceinline__ void mbar_wait(uint32_t a, uint32_t parity) {
    if (mbar_try(a, parity)) return;
    uint32_t n = 0;
    while (!mbar_try(a, parity)) {
        if (++n > kSpinLimit) __trap();
    }
}
__device__ __forceinline__ void bulk_load(uint32_t dst, const void* src, uint32_t bytes, uint32_t mbar, uint64_t pol) {
    asm volatile(
        "cp.async.bulk.shared::cluster.global.mbarrier::complete_tx::bytes.L2::cache_hint [%0], [%1], %2, [%3], %4;"
        ::"r"(dst), "l"(src), "r"(bytes), "r"(mbar), "l"(pol) : "memory");
}
__device__ __forceinline__ void tma_3d(uint32_t dst, const CUtensorMap* tm, int c0, int c1, int c2, uint32_t mbar, uint64_t pol) {
    asm volatile(
        "cp.async.bulk.tensor.3d.shared::cluster.global.mbarrier::complete_tx::bytes.L2::cache_hint "
        "[%0], [%1, {%3, %4, %5}], [%2], %6;"
        ::"r"(dst), "l"(tm), "r"(mbar), "r"(c0), "r"(c1), "r"(c2), "l"(pol) : "memory");
}
__device__ __forceinline__ void tma_2d(uint32_t dst, const CUtensorMap* tm, int c0, int c1, uint32_t mbar, uint64_t pol) {
    asm volatile(
        "cp.async.bulk.tensor.2d.shared::cluster.global.mbarrier::complete_tx::bytes.L2::cache_hint "
        "[%0], [%1, {%3, %4}], [%2], %5;"
        ::"r"(dst), "l"(tm), "r"(mbar), "r"(c0), "r"(c1), "l"(pol) : "memory");
}
__device__ __forceinline__ void ldsm_x4(uint32_t addr, uint32_t (&r)[4]) {
    asm volatile("ldmatrix.sync.aligned.m8n8.x4.shared.b16 {%0,%1,%2,%3}, [%4];"
                 : "=r"(r[0]), "=r"(r[1]), "=r"(r[2]), "=r"(r[3]) : "r"(addr) : "memory");
}
__device__ __forceinline__ void ldsm_x4_t(uint32_t addr, uint32_t (&r)[4]) {
    asm volatile("ldmatrix.sync.aligned.m8n8.x4.trans.shared.b16 {%0,%1,%2,%3}, [%4];"
                 : "=r"(r[0]), "=r"(r[1]), "=r"(r[2]), "=r"(r[3]) : "r"(addr) : "memory");
}
__device__ __forceinline__ void mma16816(float (&c)[4], uint32_t a0, uint32_t a1, uint32_t a2, uint32_t a3,
                                         uint32_t b0, uint32_t b1) {
    asm volatile(
        "mma.sync.aligned.m16n8k16.row.col.f32.bf16.bf16.f32 {%0,%1,%2,%3}, {%4,%5,%6,%7}, {%8,%9}, {%0,%1,%2,%3};"
        : "+f"(c[0]), "+f"(c[1]), "+f"(c[2]), "+f"(c[3])
        : "r"(a0), "r"(a1), "r"(a2), "r"(a3), "r"(b0), "r"(b1));
}
__device__ __forceinline__ void bar_sync(int id, int n) { asm volatile("bar.sync %0, %1;" ::"r"(id), "r"(n) : "memory"); }
__device__ __forceinline__ uint32_t lds32(uint32_t a) {
    uint32_t v; asm volatile("ld.shared.b32 %0, [%1];" : "=r"(v) : "r"(a) : "memory"); return v;
}
__device__ __forceinline__ uint4 lds128(uint32_t a) {
    uint4 v; asm volatile("ld.shared.v4.b32 {%0,%1,%2,%3}, [%4];" : "=r"(v.x), "=r"(v.y), "=r"(v.z), "=r"(v.w) : "r"(a) : "memory");
    return v;
}
__device__ __forceinline__ uint4 ld_relaxed_v4(const void* p) {
    uint4 v;
    asm volatile("ld.relaxed.gpu.global.v4.b32 {%0,%1,%2,%3}, [%4];" : "=r"(v.x), "=r"(v.y), "=r"(v.z), "=r"(v.w) : "l"(p) : "memory");
    return v;
}
__device__ __forceinline__ uint2 ld_relaxed_v2(const void* p) {
    uint2 v;
    asm volatile("ld.relaxed.gpu.global.v2.b32 {%0,%1}, [%2];" : "=r"(v.x), "=r"(v.y) : "l"(p) : "memory");
    return v;
}
__device__ __forceinline__ void st_relaxed(void* p, uint32_t v) {
    asm volatile("st.relaxed.gpu.global.b32 [%0], %1;" ::"l"(p), "r"(v) : "memory");
}
__device__ __forceinline__ void st_relaxed_v2(void* p, uint32_t a, uint32_t b) {
    asm volatile("st.relaxed.gpu.global.v2.b32 [%0], {%1,%2};" ::"l"(p), "r"(a), "r"(b) : "memory");
}
__device__ __forceinline__ unsigned long long ld_acquire_u64(const void* p) {
    unsigned long long v;
    asm volatile("ld.acquire.gpu.global.u64 %0, [%1];" : "=l"(v) : "l"(p) : "memory");
    return v;
}
__device__ __forceinline__ float bf16r(float x) { return __bfloat162float(__float2bfloat16_rn(x)); }
__device__ __forceinline__ uint32_t pack_bf16(float lo, float hi) {
    __nv_bfloat162 v = __floats2bfloat162_rn(lo, hi);
    return *reinterpret_cast<uint32_t*>(&v);
}
__device__ __forceinline__ uint32_t tagf(float v, uint32_t tag) { return (__float_as_uint(v) & ~1u) | tag; }
__device__ __forceinline__ float ex2(float x) { float y; asm("ex2.approx.ftz.f32 %0, %1;" : "=f"(y) : "f"(x)); return y; }

__device__ __forceinline__ void ffn_units(int c, int grid, int& first2, int& step2) {
    int extra = grid - kNOwner;
    if (extra > 0) {
        if (c >= kNOwner) { first2 = kNOwner + (c - kNOwner); step2 = extra; }
        else { first2 = kNFfn; step2 = 1; }
    } else {
        first2 = (c < kNFfn - kNOwner) ? kNOwner + c : kNFfn; step2 = kNFfn;
    }
}

__device__ __forceinline__ void slice_mma(uint32_t sA, uint32_t sW, float* dst, int w, int lane, uint32_t tag) {
    const int g = lane >> 2, t = lane & 3;
    uint32_t a[4] = {0u, 0u, 0u, 0u};
    if (g < 4) {
        a[0] = lds32(sA + g * 80 + t * 4);
        a[1] = lds32(sA + g * 80 + 16 + t * 4);
        a[2] = lds32(sA + g * 80 + 32 + t * 4);
        a[3] = lds32(sA + g * 80 + 48 + t * 4);
    }
    const uint32_t rowaddr = sW + lane * kWRow;
#pragma unroll 6
    for (int i = 0; i < 18; i++) {
        const int j = w * 18 + i;
        uint32_t b[4];
        ldsm_x4_t(rowaddr + j * 16, b);
        float c[4] = {0.f, 0.f, 0.f, 0.f};
        mma16816(c, a[0], 0u, a[1], 0u, b[0], b[1]);
        mma16816(c, a[2], 0u, a[3], 0u, b[2], b[3]);
        if (g < 4) st_relaxed_v2(dst + g * kD + j * 8 + t * 2, tagf(c[0], tag), tagf(c[1], tag));
    }
}

template <int NI>
__device__ __forceinline__ float slot_sum(const float* base, size_t slot_stride, uint32_t tag, uint32_t sRed,
                                          int tid, int sleep_ns) {
    const int r = tid >> 3, c4 = tid & 7;
    uint4 v[NI];
    uint32_t n = 0;
    for (;;) {
#pragma unroll
        for (int i = 0; i < NI; i++) v[i] = ld_relaxed_v4(base + (size_t)(r + 16 * i) * slot_stride + c4 * 4);
        uint32_t bad = 0;
#pragma unroll
        for (int i = 0; i < NI; i++) bad |= (v[i].x ^ tag) | (v[i].y ^ tag) | (v[i].z ^ tag) | (v[i].w ^ tag);
        if (!(bad & 1u)) break;
        if (sleep_ns) __nanosleep(sleep_ns);
        if (++n > kSpinLimit) __trap();
    }
    float s0 = 0.f, s1 = 0.f, s2 = 0.f, s3 = 0.f;
#pragma unroll
    for (int i = 0; i < NI; i++) {
        s0 += __uint_as_float(v[i].x); s1 += __uint_as_float(v[i].y);
        s2 += __uint_as_float(v[i].z); s3 += __uint_as_float(v[i].w);
    }
#pragma unroll
    for (int o = 8; o <= 16; o <<= 1) {
        s0 += __shfl_xor_sync(0xffffffffu, s0, o); s1 += __shfl_xor_sync(0xffffffffu, s1, o);
        s2 += __shfl_xor_sync(0xffffffffu, s2, o); s3 += __shfl_xor_sync(0xffffffffu, s3, o);
    }
    if ((tid & 31) < 8) {
        asm volatile("st.shared.v4.f32 [%0], {%1,%2,%3,%4};" ::"r"(sRed + (tid >> 5) * 128 + c4 * 16),
                     "f"(s0), "f"(s1), "f"(s2), "f"(s3) : "memory");
    }
    bar_sync(2, 128);
    float res = 0.f;
    if (tid < 32) {
#pragma unroll
        for (int wv = 0; wv < 4; wv++) res += __uint_as_float(lds32(sRed + wv * 128 + tid * 4));
    }
    bar_sync(2, 128);
    return res;
}

__global__ void __launch_bounds__(kThreads, 1)
fused_decode_kernel(const __grid_constant__ CUtensorMap tmK, const __grid_constant__ CUtensorMap tmV,
                    const __grid_constant__ CUtensorMap tmQ, const __grid_constant__ CUtensorMap tmG,
                    const __grid_constant__ CUtensorMap tmU,
                    const __nv_bfloat16* __restrict__ x, const __nv_bfloat16* __restrict__ wo,
                    const __nv_bfloat16* __restrict__ wdown, __nv_bfloat16* __restrict__ out) {
    extern __shared__ unsigned char smem_raw[];
    const uint32_t sbase = (smem_u32(smem_raw) + 1023u) & ~1023u;
    unsigned char* sptr = smem_raw + (sbase - smem_u32(smem_raw));
    const int tid = threadIdx.x, warp = tid >> 5, lane = tid & 31;
    const int cta = blockIdx.x, grid = gridDim.x;

    const uint32_t barFull = sbase + kOffBar, barEmpty = barFull + kNS * 8;
    const uint32_t barWFull = barEmpty + kNS * 8, barWEmpty = barWFull + 8, barQ = barWFull + 16, barEp = barWFull + 24;
    const uint32_t barWo = barWFull + 32;
    volatile int* meta = reinterpret_cast<volatile int*>(sptr + kOffMeta);
    volatile int* sProg = reinterpret_cast<volatile int*>(sptr + kOffMisc);
    volatile uint32_t* sEpoch = reinterpret_cast<volatile uint32_t*>(sptr + kOffMisc + 4);

    int f2, fstep;
    ffn_units(cta, grid, f2, fstep);
    const bool owner = cta < kNOwner;

    if (tid == 256) {
        for (int s = 0; s < kNS; s++) { mbar_init(barFull + s * 8, 1); mbar_init(barEmpty + s * 8, 4); }
        mbar_init(barWFull, 1); mbar_init(barWEmpty, 4); mbar_init(barQ, 128); mbar_init(barEp, 1); mbar_init(barWo, 1);
        *sProg = 0;
        asm volatile("fence.mbarrier_init.release.cluster;" ::: "memory");
    }
    __syncthreads();

    if (warp == 8) {
        if (lane == 0) {
            uint64_t pol;
            asm volatile("createpolicy.fractional.L2::evict_first.b64 %0, 1.0;" : "=l"(pol));
            int slot = 0; uint32_t ph = 1;
            auto next_slot = [&]() { if (++slot == kNS) { slot = 0; ph ^= 1; } };
            auto box3 = [&](const CUtensorMap* tm, int col0) {
                for (int j = 0; j < 3; j++) {
                    mbar_wait(barEmpty + slot * 8, ph);
                    mbar_expect_tx(barFull + slot * 8, kBoxBytes);
                    tma_2d(sbase + kOffRing + slot * kSlotBytes, tm, col0, j * kBoxRows, barFull + slot * 8, pol);
                    next_slot();
                }
            };
            uint32_t wph = 1;
            auto wload = [&](const __nv_bfloat16* src, uint32_t fullbar) {
                mbar_wait(barWEmpty, wph); wph ^= 1;
                mbar_expect_tx(fullbar, 32 * kD * 2);
                for (int r = 0; r < 32; r++)
                    bulk_load(sbase + kOffW + r * kWRow, src + (size_t)r * kD, kD * 2, fullbar, pol);
            };
            if (owner) box3(&tmQ, cta * 32);
            unsigned raw = atomicAdd(&g_ticket, 1u);
            if (owner) {
                box3(&tmG, cta * 32); box3(&tmU, cta * 32);
                wload(wdown + (size_t)cta * 32 * kD, barWFull);
            }
            for (int f = f2; f < kNFfn; f += fstep) {
                box3(&tmG, f * 32); box3(&tmU, f * 32);
                wload(wdown + (size_t)f * 32 * kD, barWFull);
            }
            mbar_wait(barEp, 0);
            const unsigned tbase = *sEpoch * (unsigned)(kNUnits + grid);
            for (;;) {
                const unsigned u = raw - tbase;
                if (u >= (unsigned)kNUnits) break;
                *sProg = (int)u + 1;
                raw = atomicAdd(&g_ticket, 1u);
                mbar_wait(barEmpty + slot * 8, ph);
                meta[slot] = (int)u;
                mbar_expect_tx(barFull + slot * 8, kSlotBytes);
                tma_3d(sbase + kOffRing + slot * kSlotBytes, &tmK, 0, (int)u * kUnitKeys, 0, barFull + slot * 8, pol);
                next_slot();
                mbar_wait(barEmpty + slot * 8, ph);
                mbar_expect_tx(barFull + slot * 8, kSlotBytes);
                tma_3d(sbase + kOffRing + slot * kSlotBytes, &tmV, 0, (int)u * kUnitKeys, 0, barFull + slot * 8, pol);
                next_slot();
            }
            *sProg = 0x7fffffff;
            if (owner) wload(wo + (size_t)cta * 32 * kD, barWo);
            mbar_wait(barEmpty + slot * 8, ph);
            meta[slot] = -1;
            mbar_arrive(barFull + slot * 8);
        }
    } else if (warp < 4) {
        const int w = warp, g = lane >> 2, t = lane & 3, mi = lane >> 3, r8 = lane & 7;
        {
            const uint32_t* xr = reinterpret_cast<const uint32_t*>(x + w * kD);
            float v[18];
#pragma unroll
            for (int i = 0; i < 9; i++) {
                uint32_t u = __ldg(xr + lane + 32 * i);
                v[2 * i] = __uint_as_float(u << 16); v[2 * i + 1] = __uint_as_float(u & 0xffff0000u);
            }
            float s = 0.f;
#pragma unroll
            for (int i = 0; i < 18; i++) s += v[i];
#pragma unroll
            for (int o = 16; o; o >>= 1) s += __shfl_xor_sync(0xffffffffu, s, o);
            const float mean = s * (1.f / kD);
            float q = 0.f;
#pragma unroll
            for (int i = 0; i < 18; i++) { float d = v[i] - mean; q += d * d; }
#pragma unroll
            for (int o = 16; o; o >>= 1) q += __shfl_xor_sync(0xffffffffu, q, o);
            const float mb = bf16r(mean), vb = bf16r(q * (1.f / kD));
            const float den = bf16r(sqrtf(bf16r(vb + 1e-5f)));
            uint32_t* xs = reinterpret_cast<uint32_t*>(sptr + kOffXn + w * kWRow);
#pragma unroll
            for (int i = 0; i < 9; i++)
                xs[lane + 32 * i] = pack_bf16(bf16r(v[2 * i] - mb) / den, bf16r(v[2 * i + 1] - mb) / den);
        }
        bar_sync(1, 128);

        int slot = 0; uint32_t ph = 0;
        auto next_slot = [&]() { if (++slot == kNS) { slot = 0; ph ^= 1; } };
        auto gemv3 = [&](float& o0, float& o1) {
            float c0[4] = {0.f, 0.f, 0.f, 0.f}, c1[4] = {0.f, 0.f, 0.f, 0.f};
            const uint32_t xa = sbase + kOffXn + g * kWRow + t * 4;
            for (int j = 0; j < 3; j++) {
                mbar_wait(barFull + slot * 8, ph);
                const uint32_t sb = sbase + kOffRing + slot * kSlotBytes;
#pragma unroll
                for (int kk = 0; kk < 6; kk++) {
                    const int row = kk * 32 + lane;
                    uint32_t b[4];
                    ldsm_x4_t(sb + row * 64 + ((w ^ ((row >> 1) & 3)) << 4), b);
                    uint32_t a0 = 0, a1 = 0, a2 = 0, a3 = 0;
                    if (g < 4) {
                        const uint32_t ka = xa + (j * kBoxRows + kk * 32) * 2;
                        a0 = lds32(ka); a1 = lds32(ka + 16); a2 = lds32(ka + 32); a3 = lds32(ka + 48);
                    }
                    mma16816(c0, a0, 0u, a1, 0u, b[0], b[1]);
                    mma16816(c1, a2, 0u, a3, 0u, b[2], b[3]);
                }
                __syncwarp();
                if (lane == 0) mbar_arrive(barEmpty + slot * 8);
                next_slot();
            }
            o0 = c0[0] + c1[0]; o1 = c0[1] + c1[1];
        };

        if (owner) {
            float q0, q1;
            gemv3(q0, q1);
            if (g < 4) {
                const int head = cta >> 2, quarter = cta & 3;
                const int pair = g * kHKV + (head >> 1);
                g_q[((pair * 2 + (head & 1)) * 4 + t) * 16 + quarter * 4 + w] = pack_bf16(q0, q1);
            }
            bar_sync(1, 128);
        }
        mbar_wait(barEp, 0);
        const uint32_t tag = (*sEpoch + 1u) & 1u;
        if (tid == 0) {
            __threadfence();
            asm volatile("red.release.gpu.global.add.u64 [%0], %1;" ::"l"(&g_qcount), "l"(1ull) : "memory");
        }
        uint32_t wph = 0;
        auto ffn = [&](int f) {
            float g0, g1, u0, u1;
            gemv3(g0, g1);
            gemv3(u0, u1);
            if (g < 4) {
                g0 = bf16r(g0); g1 = bf16r(g1); u0 = bf16r(u0); u1 = bf16r(u1);
                g0 = g0 > 0.f ? g0 : 0.f * g0; g1 = g1 > 0.f ? g1 : 0.f * g1;
                *reinterpret_cast<uint32_t*>(sptr + kOffHA + g * 80 + w * 16 + t * 4) = pack_bf16(g0 * u0, g1 * u1);
            }
            bar_sync(1, 128);
            mbar_wait(barWFull, wph); wph ^= 1;
            slice_mma(sbase + kOffHA, sbase + kOffW, g_dslot + (size_t)f * kB * kD, w, lane, tag);
            __syncwarp();
            if (lane == 0) mbar_arrive(barWEmpty);
            bar_sync(1, 128);
        };
        if (owner) ffn(cta);
        for (int f = f2; f < kNFfn; f += fstep) ffn(f);

        mbar_wait(barQ, 0);
        const float cs = 0.08838834764831845f * 1.4426950408889634f;
        const int krow = 16 * w + (mi & 1) * 8 + r8;
        const uint32_t koff = krow * 128;
        const int hsel = g & 1, sub = g >> 1;
        uint32_t buf = 0;
        for (;;) {
            mbar_wait(barFull + slot * 8, ph);
            const int u = meta[slot];
            if (u < 0) break;
            const int pair = u >> 7, j = u & 127;
            uint32_t qf[16];
            if (g < 2) {
                const uint32_t qa = sbase + kOffQ + ((pair * 2 + g) * 4 + t) * 64;
#pragma unroll
                for (int i = 0; i < 4; i++) {
                    uint4 v = lds128(qa + i * 16);
                    qf[4 * i] = v.x; qf[4 * i + 1] = v.y; qf[4 * i + 2] = v.z; qf[4 * i + 3] = v.w;
                }
            } else {
#pragma unroll
                for (int i = 0; i < 16; i++) qf[i] = 0u;
            }
            const uint32_t kb = sbase + kOffRing + slot * kSlotBytes + koff;
            float sA[4] = {0.f, 0.f, 0.f, 0.f}, sB[4] = {0.f, 0.f, 0.f, 0.f};
#pragma unroll
            for (int ks = 0; ks < 8; ks++) {
                uint32_t a[4];
                const int chunk = (ks & 3) * 2 + (mi >> 1);
                ldsm_x4(kb + (ks >> 2) * 8192 + ((chunk ^ r8) << 4), a);
                if (ks & 1) mma16816(sB, a[0], a[1], a[2], a[3], qf[2 * ks], qf[2 * ks + 1]);
                else        mma16816(sA, a[0], a[1], a[2], a[3], qf[2 * ks], qf[2 * ks + 1]);
            }
            __syncwarp();
            if (lane == 0) mbar_arrive(barEmpty + slot * 8);
            next_slot();
            float* sS = reinterpret_cast<float*>(sptr + kOffS) + buf * 144;
            if (t == 0) {
                sS[16 * w + g] = sA[0] + sB[0];      sS[72 + 16 * w + g] = sA[1] + sB[1];
                sS[16 * w + g + 8] = sA[2] + sB[2];  sS[72 + 16 * w + g + 8] = sA[3] + sB[3];
            }
            mbar_wait(barFull + slot * 8, ph);
            bar_sync(1, 128);
            const uint32_t vb = sbase + kOffRing + slot * kSlotBytes + (w >> 1) * 8192;
            uint32_t va[4][2][4];
#pragma unroll
            for (int ks = 0; ks < 4; ks++)
#pragma unroll
                for (int mt = 0; mt < 2; mt++) {
                    const int key = 16 * ks + (mi >> 1) * 8 + r8;
                    const int chunk = (w & 1) * 4 + mt * 2 + (mi & 1);
                    ldsm_x4_t(vb + key * 128 + ((chunk ^ r8) << 4), va[ks][mt]);
                }
            const float2 s01 = *reinterpret_cast<const float2*>(sS + hsel * 72 + 16 * sub + 2 * t);
            const float2 s23 = *reinterpret_cast<const float2*>(sS + hsel * 72 + 16 * sub + 2 * t + 8);
            float mx = fmaxf(fmaxf(s01.x, s01.y), fmaxf(s23.x, s23.y));
            mx = fmaxf(mx, __shfl_xor_sync(0xffffffffu, mx, 1));
            mx = fmaxf(mx, __shfl_xor_sync(0xffffffffu, mx, 2));
            mx = fmaxf(mx, __shfl_xor_sync(0xffffffffu, mx, 8));
            mx = fmaxf(mx, __shfl_xor_sync(0xffffffffu, mx, 16));
            const uint32_t mtag = tagf(mx * cs, tag);
            const float mt_ = __uint_as_float(mtag);
            const float p0 = ex2(fmaf(s01.x, cs, -mt_)), p1 = ex2(fmaf(s01.y, cs, -mt_));
            const float p2 = ex2(fmaf(s23.x, cs, -mt_)), p3 = ex2(fmaf(s23.y, cs, -mt_));
            const uint32_t pk0 = pack_bf16(p0, p1), pk1 = pack_bf16(p2, p3);
            float o[2][4] = {{0.f, 0.f, 0.f, 0.f}, {0.f, 0.f, 0.f, 0.f}};
#pragma unroll
            for (int ks = 0; ks < 4; ks++) {
                const uint32_t b0 = (sub == ks) ? pk0 : 0u, b1 = (sub == ks) ? pk1 : 0u;
                mma16816(o[0], va[ks][0][0], va[ks][0][1], va[ks][0][2], va[ks][0][3], b0, b1);
                mma16816(o[1], va[ks][1][0], va[ks][1][1], va[ks][1][2], va[ks][1][3], b0, b1);
            }
            __syncwarp();
            if (lane == 0) mbar_arrive(barEmpty + slot * 8);
            next_slot();
            float k4[4];
#pragma unroll
            for (int i = 0; i < 4; i++) {
                const float send = (t & 1) ? o[0][i] : o[1][i];
                const float keep = (t & 1) ? o[1][i] : o[0][i];
                k4[i] = keep + __shfl_xor_sync(0xffffffffu, send, 1);
            }
            float k2[2];
#pragma unroll
            for (int i = 0; i < 2; i++) {
                const float send = (t & 2) ? k4[i] : k4[2 + i];
                const float keep = (t & 2) ? k4[2 + i] : k4[i];
                k2[i] = keep + __shfl_xor_sync(0xffffffffu, send, 2);
            }
            const int dl = 16 * (t & 1) + 8 * (t >> 1) + g;
            float* po = g_part_o + ((size_t)((pair * 2) * 4 + w) * kUnitsPerPair + j) * 32 + dl;
            st_relaxed(po, tagf(k2[0], tag));
            st_relaxed(po + 4 * kUnitsPerPair * 32, tagf(k2[1], tag));
            if (w == 0) {
                float l = (p0 + p1) + (p2 + p3);
                l += __shfl_xor_sync(0xffffffffu, l, 1);
                l += __shfl_xor_sync(0xffffffffu, l, 2);
                l += __shfl_xor_sync(0xffffffffu, l, 8);
                l += __shfl_xor_sync(0xffffffffu, l, 16);
                if (t == 0 && g < 2)
                    st_relaxed_v2(g_part_ml + ((size_t)(pair * 2 + g) * kUnitsPerPair + j) * 2, mtag, tagf(l, tag));
            }
            buf ^= 1;
        }
    } else {
        const int bt = tid - 128, w = warp - 4;
        unsigned long long target = 0;
        if (bt == 0) {
            const unsigned long long c0 = ld_acquire_u64(&g_qcount);
            const unsigned long long e = c0 / (unsigned long long)grid;
            *sEpoch = (uint32_t)e;
            mbar_arrive(barEp);
            target = (e + 1) * (unsigned long long)grid;
        }
        const bool fin = cta < kNFin;
        const int fb = cta / 18, fn0 = (cta % 18) * 32;
        float xval = 0.f;
        if (fin && bt < 32) xval = __bfloat162float(x[fb * kD + fn0 + bt]);
        if (bt == 0) {
            uint32_t n = 0;
            while (ld_acquire_u64(&g_qcount) < target) {
                __nanosleep(64);
                if (++n > kSpinLimit) __trap();
            }
        }
        bar_sync(2, 128);
        {
            const uint4* src = reinterpret_cast<const uint4*>(g_q);
            uint4 v[16];
#pragma unroll
            for (int i = 0; i < 16; i++) v[i] = __ldcg(src + bt + 128 * i);
            uint4* dstq = reinterpret_cast<uint4*>(sptr + kOffQ);
#pragma unroll
            for (int i = 0; i < 16; i++) dstq[bt + 128 * i] = v[i];
        }
        mbar_arrive(barQ);
        const uint32_t tag = (*sEpoch + 1u) & 1u;
        const uint32_t sRed = sbase + kOffRed;
        float gate = 0.f;
        if (fin) {
            const float dsum = slot_sum<9>(g_dslot + fb * kD + fn0, (size_t)kB * kD, tag, sRed, bt, 500);
            const float d = bf16r(dsum);
            gate = bf16r(d / (1.f + __expf(-d)));
        }
        if (owner) {
            const int hkv = cta >> 3, hh = (cta >> 2) & 1, quarter = cta & 3;
            const int r = bt >> 3, c4 = bt & 7;
            for (int b = 0; b < kB; b++) {
                const int pair = b * kHKV + hkv;
                {
                    uint32_t n = 0;
                    while (*sProg < (pair + 1) * kUnitsPerPair) {
                        __nanosleep(200);
                        if (++n > kSpinLimit) __trap();
                    }
                }
                const float* po = g_part_o + ((size_t)((pair * 2 + hh) * 4 + quarter) * kUnitsPerPair + r) * 32 + c4 * 4;
                const float* pml = g_part_ml + ((size_t)(pair * 2 + hh) * kUnitsPerPair + lane) * 2;
                uint4 v[8]; uint2 ml[4];
                uint32_t n = 0;
                for (;;) {
#pragma unroll
                    for (int i = 0; i < 4; i++) ml[i] = ld_relaxed_v2(pml + i * 64);
#pragma unroll
                    for (int i = 0; i < 8; i++) v[i] = ld_relaxed_v4(po + i * 16 * 32);
                    uint32_t bad = 0;
#pragma unroll
                    for (int i = 0; i < 4; i++) bad |= (ml[i].x ^ tag) | (ml[i].y ^ tag);
#pragma unroll
                    for (int i = 0; i < 8; i++) bad |= (v[i].x ^ tag) | (v[i].y ^ tag) | (v[i].z ^ tag) | (v[i].w ^ tag);
                    if (!__any_sync(0xffffffffu, bad & 1u)) break;
                    if (++n > kSpinLimit) __trap();
                }
                float M = fmaxf(fmaxf(__uint_as_float(ml[0].x), __uint_as_float(ml[1].x)),
                                fmaxf(__uint_as_float(ml[2].x), __uint_as_float(ml[3].x)));
#pragma unroll
                for (int o = 16; o; o >>= 1) M = fmaxf(M, __shfl_xor_sync(0xffffffffu, M, o));
                float wt[4], L = 0.f;
#pragma unroll
                for (int i = 0; i < 4; i++) {
                    wt[i] = ex2(__uint_as_float(ml[i].x) - M);
                    L = fmaf(wt[i], __uint_as_float(ml[i].y), L);
                }
#pragma unroll
                for (int o = 16; o; o >>= 1) L += __shfl_xor_sync(0xffffffffu, L, o);
                float a0 = 0.f, a1 = 0.f, a2 = 0.f, a3 = 0.f;
#pragma unroll
                for (int i = 0; i < 8; i++) {
                    const float wi = __shfl_sync(0xffffffffu, wt[i >> 1], r + 16 * (i & 1));
                    a0 = fmaf(wi, __uint_as_float(v[i].x), a0); a1 = fmaf(wi, __uint_as_float(v[i].y), a1);
                    a2 = fmaf(wi, __uint_as_float(v[i].z), a2); a3 = fmaf(wi, __uint_as_float(v[i].w), a3);
                }
#pragma unroll
                for (int o = 8; o <= 16; o <<= 1) {
                    a0 += __shfl_xor_sync(0xffffffffu, a0, o); a1 += __shfl_xor_sync(0xffffffffu, a1, o);
                    a2 += __shfl_xor_sync(0xffffffffu, a2, o); a3 += __shfl_xor_sync(0xffffffffu, a3, o);
                }
                if (lane < 8)
                    asm volatile("st.shared.v4.f32 [%0], {%1,%2,%3,%4};" ::"r"(sRed + w * 128 + c4 * 16),
                                 "f"(a0), "f"(a1), "f"(a2), "f"(a3) : "memory");
                bar_sync(2, 128);
                if (bt < 32) {
                    float o = 0.f;
#pragma unroll
                    for (int wv = 0; wv < 4; wv++) o += __uint_as_float(lds32(sRed + wv * 128 + bt * 4));
                    *reinterpret_cast<__nv_bfloat16*>(sptr + kOffOA + b * 80 + bt * 2) = __float2bfloat16_rn(o / L);
                }
                bar_sync(2, 128);
            }
            mbar_wait(barWo, 0);
            slice_mma(sbase + kOffOA, sbase + kOffW, g_sslot + (size_t)cta * kB * kD, w, lane, tag);
        }
        if (fin) {
            const float ssum = slot_sum<8>(g_sslot + fb * kD + fn0, (size_t)kB * kD, tag, sRed, bt, 0);
            if (bt < 32) {
                const float sg = bf16r(bf16r(ssum) * gate);
                out[fb * kD + fn0 + bt] = __float2bfloat16_rn(xval + sg);
            }
        }
    }
}

typedef CUresult (*EncodeFn)(CUtensorMap*, CUtensorMapDataType, cuuint32_t, void*, const cuuint64_t*,
                             const cuuint64_t*, const cuuint32_t*, const cuuint32_t*, CUtensorMapInterleave,
                             CUtensorMapSwizzle, CUtensorMapL2promotion, CUtensorMapFloatOOBfill);

struct HostState {
    bool init;
    int grid;
    const void* ptr[5];
    CUtensorMap tm[5];
};
HostState g_host;

}

extern "C" void kernel_launch(void* const* d_in, const int* in_sizes, int n_in, void* d_out, int out_size) {
    (void)in_sizes; (void)n_in; (void)out_size;
    const __nv_bfloat16* x = (const __nv_bfloat16*)d_in[0];
    void* kc = d_in[1];
    void* vc = d_in[2];
    void* wq = d_in[3];
    const __nv_bfloat16* wo = (const __nv_bfloat16*)d_in[4];
    void* wg = d_in[6];
    void* wu = d_in[7];
    const __nv_bfloat16* wd = (const __nv_bfloat16*)d_in[8];

    HostState& hs = g_host;
    const void* ptrs[5] = {kc, vc, wq, wg, wu};
    bool need = !hs.init;
    for (int i = 0; i < 5 && !need; i++) need = hs.ptr[i] != ptrs[i];
    if (need) {
        EncodeFn enc = nullptr;
        cudaDriverEntryPointQueryResult qr;
        cudaGetDriverEntryPoint("cuTensorMapEncodeTiled", (void**)&enc, cudaEnableDefault, &qr);
        if (!enc) return;
        const cuuint32_t es[3] = {1, 1, 1};
        for (int i = 0; i < 2; i++) {
            const cuuint64_t gd[3] = {64, (cuuint64_t)kNPair * kSK, 2};
            const cuuint64_t gs[2] = {256, 128};
            const cuuint32_t bx[3] = {64, kUnitKeys, 2};
            enc(&hs.tm[i], CU_TENSOR_MAP_DATA_TYPE_BFLOAT16, 3, (void*)ptrs[i], gd, gs, bx, es,
                CU_TENSOR_MAP_INTERLEAVE_NONE, CU_TENSOR_MAP_SWIZZLE_128B, CU_TENSOR_MAP_L2_PROMOTION_L2_128B,
                CU_TENSOR_MAP_FLOAT_OOB_FILL_NONE);
        }
        for (int i = 2; i < 5; i++) {
            const cuuint64_t ncol = (i == 2) ? (cuuint64_t)kHQ * kDH : (cuuint64_t)kF;
            const cuuint64_t gd[2] = {ncol, (cuuint64_t)kD};
            const cuuint64_t gs[1] = {ncol * 2};
            const cuuint32_t bx[2] = {32, kBoxRows};
            enc(&hs.tm[i], CU_TENSOR_MAP_DATA_TYPE_BFLOAT16, 2, (void*)ptrs[i], gd, gs, bx, es,
                CU_TENSOR_MAP_INTERLEAVE_NONE, CU_TENSOR_MAP_SWIZZLE_64B, CU_TENSOR_MAP_L2_PROMOTION_L2_128B,
                CU_TENSOR_MAP_FLOAT_OOB_FILL_NONE);
        }
        for (int i = 0; i < 5; i++) hs.ptr[i] = ptrs[i];
        if (!hs.init) {
            int dev = 0, sms = 0;
            cudaGetDevice(&dev);
            cudaDeviceGetAttribute(&sms, cudaDevAttrMultiProcessorCount, dev);
            cudaFuncSetAttribute(fused_decode_kernel, cudaFuncAttributeMaxDynamicSharedMemorySize, kSmemBytes);
            hs.grid = sms > kMaxGrid ? kMaxGrid : sms;
            hs.init = true;
        }
    }
    if (hs.grid < kNOwner) return;
    fused_decode_kernel<<<hs.grid, kThreads, kSmemBytes, cudaStreamPerThread>>>(
        hs.tm[0], hs.tm[1], hs.tm[2], hs.tm[3], hs.tm[4], x, wo, wd, (__nv_bfloat16*)d_out);
}
```

```cpp
#include <cuda_runtime.h>
#include <cuda_bf16.h>
#include <cuda.h>
#include <stdint.h>

namespace {

constexpr int kB = 4, kD = 576, kHQ = 32, kHKV = 16, kSK = 8192, kDH = 128, kF = 4608;
constexpr int kNPair = kB * kHKV;
constexpr int kUnitKeys = 64;
constexpr int kUnitsPerPair = kSK / kUnitKeys;
constexpr int kNUnits = kNPair * kUnitsPerPair;
constexpr int kNOwner = 128;
constexpr int kNFfn = kF / 32;
constexpr int kNFin = (kB * kD) / 32;
constexpr int kMaxGrid = 144;

constexpr int kNS = 9;
constexpr int kInfl = 3;
constexpr int kInflBox = 4;
constexpr int kSlotBytes = 16384;
constexpr int kXRow = 1168;
constexpr int kWBytes = 32 * kD * 2;
constexpr int kBoxRows = 192;
constexpr int kBoxBytes = kBoxRows * 64;

constexpr int kOffRing = 0;
constexpr int kOffW = kOffRing + kNS * kSlotBytes;
constexpr int kOffQ = kOffW + kWBytes;
constexpr int kOffXn = kOffQ + 32768;
constexpr int kOffS = kOffXn + 4 * kXRow;
constexpr int kOffHA = kOffS + 2 * 320;
constexpr int kOffHB = kOffHA + 4 * 80;
constexpr int kOffOA = kOffHB + 4 * 80;
constexpr int kOffQS = kOffOA + 4 * 80;
constexpr int kOffRed = kOffQS + 512;
constexpr int kOffBar = kOffRed + 3 * 512;
constexpr int kNBar = 2 * kNS + 9;
constexpr int kOffMeta = kOffBar + kNBar * 8;
constexpr int kOffMisc = kOffMeta + kNS * 4;
constexpr int kSmemUsed = kOffMisc + 16;
constexpr int kSmemBytes = kSmemUsed + 1024;
static_assert(kOffW % 1024 == 0 && kOffQ % 16 == 0 && kOffXn % 16 == 0 && kOffS % 16 == 0, "align");
static_assert(kOffQS % 16 == 0 && kOffRed % 16 == 0 && kOffBar % 8 == 0, "align");
static_assert(kSmemBytes <= 232448, "smem");
static_assert(kNS >= 6 && kInfl < kNS && kInflBox < kNS, "ring");

constexpr int kThreads = 288;
constexpr uint32_t kSpinLimit = 1u << 22;

__device__ __align__(256) float g_part_o[(size_t)kNPair * 2 * 4 * kUnitsPerPair * 32];
__device__ __align__(256) float g_part_ml[(size_t)kNPair * kUnitsPerPair * 8];
__device__ __align__(256) float g_dslot[(size_t)kNFfn * kB * kD];
__device__ __align__(256) float g_sslot[(size_t)kNOwner * kB * kD];
__device__ __align__(256) uint32_t g_q[kB * kHQ * kDH];
__device__ __align__(256) unsigned int g_hint[kNPair * 32];
__device__ __align__(256) unsigned long long g_qcount_[32];
__device__ __align__(256) unsigned int g_ticket_[64];
#define g_qcount g_qcount_[0]
#define g_ticket g_ticket_[0]

__device__ __forceinline__ uint32_t smem_u32(const void* p) { return (uint32_t)__cvta_generic_to_shared(p); }
__device__ __forceinline__ void mbar_init(uint32_t a, uint32_t c) {
    asm volatile("mbarrier.init.shared::cta.b64 [%0], %1;" ::"r"(a), "r"(c) : "memory");
}
__device__ __forceinline__ void mbar_expect_tx(uint32_t a, uint32_t bytes) {
    asm volatile("mbarrier.arrive.expect_tx.shared::cta.b64 _, [%0], %1;" ::"r"(a), "r"(bytes) : "memory");
}
__device__ __forceinline__ void mbar_arrive(uint32_t a) {
    asm volatile("mbarrier.arrive.shared::cta.b64 _, [%0];" ::"r"(a) : "memory");
}
__device__ __forceinline__ bool mbar_try(uint32_t a, uint32_t parity) {
    uint32_t ok;
    asm volatile(
        "{\n.reg .pred p;\n"
        "mbarrier.try_wait.parity.shared::cta.b64 p, [%1], %2;\n"
        "selp.u32 %0, 1, 0, p;\n}"
        : "=r"(ok) : "r"(a), "r"(parity) : "memory");
    return ok != 0;
}
__device__ __forceinline__ void mbar_wait(uint32_t a, uint32_t parity) {
    uint32_t n = 0;
    while (!mbar_try(a, parity)) {
        if (++n > kSpinLimit) __trap();
    }
}
__device__ __forceinline__ void tma_3d(uint32_t dst, const CUtensorMap* tm, int c0, int c1, int c2, uint32_t mbar, uint64_t pol) {
    asm volatile(
        "cp.async.bulk.tensor.3d.shared::cluster.global.mbarrier::complete_tx::bytes.L2::cache_hint "
        "[%0], [%1, {%3, %4, %5}], [%2], %6;"
        ::"r"(dst), "l"(tm), "r"(mbar), "r"(c0), "r"(c1), "r"(c2), "l"(pol) : "memory");
}
__device__ __forceinline__ void tma_2d(uint32_t dst, const CUtensorMap* tm, int c0, int c1, uint32_t mbar, uint64_t pol) {
    asm volatile(
        "cp.async.bulk.tensor.2d.shared::cluster.global.mbarrier::complete_tx::bytes.L2::cache_hint "
        "[%0], [%1, {%3, %4}], [%2], %5;"
        ::"r"(dst), "l"(tm), "r"(mbar), "r"(c0), "r"(c1), "l"(pol) : "memory");
}
__device__ __forceinline__ void ldsm_x4(uint32_t addr, uint32_t (&r)[4]) {
    asm volatile("ldmatrix.sync.aligned.m8n8.x4.shared.b16 {%0,%1,%2,%3}, [%4];"
                 : "=r"(r[0]), "=r"(r[1]), "=r"(r[2]), "=r"(r[3]) : "r"(addr) : "memory");
}
__device__ __forceinline__ void ldsm_x4_t(uint32_t addr, uint32_t (&r)[4]) {
    asm volatile("ldmatrix.sync.aligned.m8n8.x4.trans.shared.b16 {%0,%1,%2,%3}, [%4];"
                 : "=r"(r[0]), "=r"(r[1]), "=r"(r[2]), "=r"(r[3]) : "r"(addr) : "memory");
}
__device__ __forceinline__ void mma16816(float (&c)[4], uint32_t a0, uint32_t a1, uint32_t a2, uint32_t a3,
                                         uint32_t b0, uint32_t b1) {
    asm volatile(
        "mma.sync.aligned.m16n8k16.row.col.f32.bf16.bf16.f32 {%0,%1,%2,%3}, {%4,%5,%6,%7}, {%8,%9}, {%0,%1,%2,%3};"
        : "+f"(c[0]), "+f"(c[1]), "+f"(c[2]), "+f"(c[3])
        : "r"(a0), "r"(a1), "r"(a2), "r"(a3), "r"(b0), "r"(b1));
}
__device__ __forceinline__ void bar_sync(int id, int n) { asm volatile("bar.sync %0, %1;" ::"r"(id), "r"(n) : "memory"); }
__device__ __forceinline__ uint32_t lds32(uint32_t a) {
    uint32_t v; asm volatile("ld.shared.b32 %0, [%1];" : "=r"(v) : "r"(a) : "memory"); return v;
}
__device__ __forceinline__ uint2 lds64(uint32_t a) {
    uint2 v; asm volatile("ld.shared.v2.b32 {%0,%1}, [%2];" : "=r"(v.x), "=r"(v.y) : "r"(a) : "memory"); return v;
}
__device__ __forceinline__ uint4 lds128(uint32_t a) {
    uint4 v; asm volatile("ld.shared.v4.b32 {%0,%1,%2,%3}, [%4];" : "=r"(v.x), "=r"(v.y), "=r"(v.z), "=r"(v.w) : "r"(a) : "memory");
    return v;
}
__device__ __forceinline__ void sts32(uint32_t a, uint32_t v) { asm volatile("st.shared.b32 [%0], %1;" ::"r"(a), "r"(v) : "memory"); }
__device__ __forceinline__ void sts64(uint32_t a, uint32_t x, uint32_t y) {
    asm volatile("st.shared.v2.b32 [%0], {%1,%2};" ::"r"(a), "r"(x), "r"(y) : "memory");
}
__device__ __forceinline__ void sts128f(uint32_t a, float x, float y, float z, float w) {
    asm volatile("st.shared.v4.f32 [%0], {%1,%2,%3,%4};" ::"r"(a), "f"(x), "f"(y), "f"(z), "f"(w) : "memory");
}
__device__ __forceinline__ uint32_t hmax2(uint32_t a, uint32_t b) {
    uint32_t d; asm("max.bf16x2 %0, %1, %2;" : "=r"(d) : "r"(a), "r"(b)); return d;
}
__device__ __forceinline__ uint4 ld_relaxed_v4(const void* p) {
    uint4 v;
    asm volatile("ld.relaxed.gpu.global.v4.b32 {%0,%1,%2,%3}, [%4];" : "=r"(v.x), "=r"(v.y), "=r"(v.z), "=r"(v.w) : "l"(p) : "memory");
    return v;
}
__device__ __forceinline__ uint32_t ld_relaxed(const void* p) {
    uint32_t v;
    asm volatile("ld.relaxed.gpu.global.b32 %0, [%1];" : "=r"(v) : "l"(p) : "memory");
    return v;
}
__device__ __forceinline__ unsigned long long ld_relaxed_u64(const void* p) {
    unsigned long long v;
    asm volatile("ld.relaxed.gpu.global.u64 %0, [%1];" : "=l"(v) : "l"(p) : "memory");
    return v;
}
template <int STRIDE>
__device__ __forceinline__ void ld8_v4_masked(uint4 (&v)[8], const void* p, uint32_t mask) {
    asm volatile(
        "{\n.reg .pred p;\n.reg .b32 t;\n"
        "and.b32 t, %33, 1;\nsetp.ne.u32 p, t, 0;\n@p ld.relaxed.gpu.global.v4.b32 {%0,%1,%2,%3}, [%32+%34];\n"
        "and.b32 t, %33, 2;\nsetp.ne.u32 p, t, 0;\n@p ld.relaxed.gpu.global.v4.b32 {%4,%5,%6,%7}, [%32+%35];\n"
        "and.b32 t, %33, 4;\nsetp.ne.u32 p, t, 0;\n@p ld.relaxed.gpu.global.v4.b32 {%8,%9,%10,%11}, [%32+%36];\n"
        "and.b32 t, %33, 8;\nsetp.ne.u32 p, t, 0;\n@p ld.relaxed.gpu.global.v4.b32 {%12,%13,%14,%15}, [%32+%37];\n"
        "and.b32 t, %33, 16;\nsetp.ne.u32 p, t, 0;\n@p ld.relaxed.gpu.global.v4.b32 {%16,%17,%18,%19}, [%32+%38];\n"
        "and.b32 t, %33, 32;\nsetp.ne.u32 p, t, 0;\n@p ld.relaxed.gpu.global.v4.b32 {%20,%21,%22,%23}, [%32+%39];\n"
        "and.b32 t, %33, 64;\nsetp.ne.u32 p, t, 0;\n@p ld.relaxed.gpu.global.v4.b32 {%24,%25,%26,%27}, [%32+%40];\n"
        "and.b32 t, %33, 128;\nsetp.ne.u32 p, t, 0;\n@p ld.relaxed.gpu.global.v4.b32 {%28,%29,%30,%31}, [%32+%41];\n"
        "}"
        : "+r"(v[0].x), "+r"(v[0].y), "+r"(v[0].z), "+r"(v[0].w), "+r"(v[1].x), "+r"(v[1].y), "+r"(v[1].z), "+r"(v[1].w), "+r"(v[2].x), "+r"(v[2].y), "+r"(v[2].z), "+r"(v[2].w), "+r"(v[3].x), "+r"(v[3].y), "+r"(v[3].z), "+r"(v[3].w), "+r"(v[4].x), "+r"(v[4].y), "+r"(v[4].z), "+r"(v[4].w), "+r"(v[5].x), "+r"(v[5].y), "+r"(v[5].z), "+r"(v[5].w), "+r"(v[6].x), "+r"(v[6].y), "+r"(v[6].z), "+r"(v[6].w), "+r"(v[7].x), "+r"(v[7].y), "+r"(v[7].z), "+r"(v[7].w)
        : "l"(p), "r"(mask), "n"(0 * STRIDE), "n"(1 * STRIDE), "n"(2 * STRIDE), "n"(3 * STRIDE), "n"(4 * STRIDE), "n"(5 * STRIDE), "n"(6 * STRIDE), "n"(7 * STRIDE)
        : "memory");
}
template <int STRIDE>
__device__ __forceinline__ void ld4_v2_masked(uint2 (&v)[4], const void* p, uint32_t mask) {
    asm volatile(
        "{\n.reg .pred p;\n.reg .b32 t;\n"
        "and.b32 t, %9, 1;\nsetp.ne.u32 p, t, 0;\n@p ld.relaxed.gpu.global.v2.b32 {%0,%1}, [%8+%10];\n"
        "and.b32 t, %9, 2;\nsetp.ne.u32 p, t, 0;\n@p ld.relaxed.gpu.global.v2.b32 {%2,%3}, [%8+%11];\n"
        "and.b32 t, %9, 4;\nsetp.ne.u32 p, t, 0;\n@p ld.relaxed.gpu.global.v2.b32 {%4,%5}, [%8+%12];\n"
        "and.b32 t, %9, 8;\nsetp.ne.u32 p, t, 0;\n@p ld.relaxed.gpu.global.v2.b32 {%6,%7}, [%8+%13];\n"
        "}"
        : "+r"(v[0].x), "+r"(v[0].y), "+r"(v[1].x), "+r"(v[1].y), "+r"(v[2].x), "+r"(v[2].y), "+r"(v[3].x), "+r"(v[3].y)
        : "l"(p), "r"(mask), "n"(0 * STRIDE), "n"(1 * STRIDE), "n"(2 * STRIDE), "n"(3 * STRIDE)
        : "memory");
}
__device__ __forceinline__ uint32_t bad4(const uint4& v, uint32_t tag) {
    return ((v.x ^ tag) | (v.y ^ tag) | (v.z ^ tag) | (v.w ^ tag)) & 1u;
}
__device__ __forceinline__ void st_relaxed(void* p, uint32_t v) {
    asm volatile("st.relaxed.gpu.global.b32 [%0], %1;" ::"l"(p), "r"(v) : "memory");
}
__device__ __forceinline__ void st_relaxed_v2(void* p, uint32_t a, uint32_t b) {
    asm volatile("st.relaxed.gpu.global.v2.b32 [%0], {%1,%2};" ::"l"(p), "r"(a), "r"(b) : "memory");
}
__device__ __forceinline__ void st_relaxed_v4(void* p, uint32_t a, uint32_t b, uint32_t c, uint32_t d) {
    asm volatile("st.relaxed.gpu.global.v4.b32 [%0], {%1,%2,%3,%4};" ::"l"(p), "r"(a), "r"(b), "r"(c), "r"(d) : "memory");
}
__device__ __forceinline__ float bf16r(float x) { return __bfloat162float(__float2bfloat16_rn(x)); }
__device__ __forceinline__ uint32_t pack_bf16(float lo, float hi) {
    __nv_bfloat162 v = __floats2bfloat162_rn(lo, hi);
    return *reinterpret_cast<uint32_t*>(&v);
}
__device__ __forceinline__ uint32_t tagf(float v, uint32_t tag) { return (__float_as_uint(v) & ~1u) | tag; }
__device__ __forceinline__ float untag(uint32_t w) { return __uint_as_float(w & ~1u); }
__device__ __forceinline__ float ex2(float x) { float y; asm("ex2.approx.ftz.f32 %0, %1;" : "=f"(y) : "f"(x)); return y; }

__device__ __forceinline__ void ffn_units(int c, int grid, int& first2, int& step2) {
    const int extra = grid - kNOwner;
    if (extra > 0) {
        if (c >= kNOwner) { first2 = c; step2 = extra; }
        else { first2 = kNFfn; step2 = 1; }
    } else {
        first2 = (c < kNFfn - kNOwner) ? kNOwner + c : kNFfn; step2 = kNFfn;
    }
}

__device__ __noinline__ void slice_mma(uint32_t sA, uint32_t sW, float* dst, int w, int lane, uint32_t tag) {
    const int g = lane >> 2, t = lane & 3, mi = lane >> 3;
    const int row = (mi >> 1) * 8 + (lane & 7);
    uint32_t a[9][2][4];
#pragma unroll
    for (int i = 0; i < 9; i++) {
        const uint32_t chunk = (w * 9 + i) * 2 + (mi & 1);
#pragma unroll
        for (int ks = 0; ks < 2; ks++)
            ldsm_x4_t(sW + (row + ks * 16) * (kD * 2) + ((chunk ^ ((row + (chunk >> 3)) & 7u)) << 4), a[i][ks]);
    }
    const uint32_t ba = sA + (g & 3) * 80 + t * 4;
    const uint32_t b0 = lds32(ba), b1 = lds32(ba + 16), b2 = lds32(ba + 32), b3 = lds32(ba + 48);
    float* d = dst + (w * 144 + g + (t >> 1) * 8) * 4 + (t & 1) * 2;
    float c[9][4];
#pragma unroll
    for (int i = 0; i < 9; i++) {
        c[i][0] = c[i][1] = c[i][2] = c[i][3] = 0.f;
        mma16816(c[i], a[i][0][0], a[i][0][1], a[i][0][2], a[i][0][3], b0, b1);
    }
#pragma unroll
    for (int i = 0; i < 9; i++) mma16816(c[i], a[i][1][0], a[i][1][1], a[i][1][2], a[i][1][3], b2, b3);
#pragma unroll
    for (int i = 0; i < 9; i++)
        st_relaxed_v2(d + i * 64, tagf(t < 2 ? c[i][0] : c[i][2], tag), tagf(t < 2 ? c[i][1] : c[i][3], tag));
}

__device__ __noinline__ float finish(int off, int mode, uint32_t tag, uint32_t sRed, int tid, float gate, float xval,
                                     __nv_bfloat16* out) {
    const int r = tid >> 3, c4 = tid & 7;
    const float* p = (mode == 1 ? g_dslot : g_sslot) + (size_t)r * (kB * kD) + off + c4 * 4;
    uint4 v[8], v8 = make_uint4(tag, tag, tag, tag);
#pragma unroll
    for (int i = 0; i < 8; i++) v[i] = v8;
    uint32_t pend = mode ? 0xffu : 0u, p8 = mode == 1, n = 0;
    for (;;) {
        if (p8) v8 = ld_relaxed_v4(p + (size_t)8 * 16 * (kB * kD));
        ld8_v4_masked<16 * kB * kD * 4>(v, p, pend);
        pend = 0;
#pragma unroll
        for (int i = 0; i < 8; i++) pend |= bad4(v[i], tag) << i;
        p8 = bad4(v8, tag);
        if (!(pend | p8)) break;
        if (++n > kSpinLimit) __trap();
    }
    __syncwarp();
    float s0, s1, s2, s3;
#define SUM9(f) (((untag(v[0].f) + untag(v[1].f)) + (untag(v[2].f) + untag(v[3].f))) + \
                 ((untag(v[4].f) + untag(v[5].f)) + (untag(v[6].f) + untag(v[7].f))) + untag(v8.f))
    s0 = SUM9(x); s1 = SUM9(y); s2 = SUM9(z); s3 = SUM9(w);
#undef SUM9
    const bool h3 = (tid & 8) != 0, h4 = (tid & 16) != 0;
    const float k0 = (h3 ? s2 : s0) + __shfl_xor_sync(0xffffffffu, h3 ? s0 : s2, 8);
    const float k1 = (h3 ? s3 : s1) + __shfl_xor_sync(0xffffffffu, h3 ? s1 : s3, 8);
    const float k = (h4 ? k1 : k0) + __shfl_xor_sync(0xffffffffu, h4 ? k0 : k1, 16);
    sts32(sRed + (tid >> 5) * 128 + (c4 * 4 + (h3 ? 2 : 0) + (h4 ? 1 : 0)) * 4, __float_as_uint(k));
    bar_sync(2, 128);
    float res = 0.f;
    if (tid < 32) {
        res = (__uint_as_float(lds32(sRed + tid * 4)) + __uint_as_float(lds32(sRed + 128 + tid * 4))) +
              (__uint_as_float(lds32(sRed + 256 + tid * 4)) + __uint_as_float(lds32(sRed + 384 + tid * 4)));
        res = bf16r(res);
        const __nv_bfloat16 o = __float2bfloat16_rn(xval + bf16r(res * gate));
        if (mode == 2) out[(tid & 3) * kD + (off >> 2) + (tid >> 2)] = o;
        res = bf16r(__fdividef(res, 1.f + __expf(-res)));
    }
    return res;
}

__global__ void __launch_bounds__(kThreads, 1)
fused_decode_kernel(const __grid_constant__ CUtensorMap tmK, const __grid_constant__ CUtensorMap tmV,
                    const __grid_constant__ CUtensorMap tmQ, const __grid_constant__ CUtensorMap tmG,
                    const __grid_constant__ CUtensorMap tmU, const __grid_constant__ CUtensorMap tmD,
                    const __grid_constant__ CUtensorMap tmO,
                    const __nv_bfloat16* __restrict__ x, __nv_bfloat16* __restrict__ out) {
    extern __shared__ unsigned char smem_raw[];
    const uint32_t sbase = (smem_u32(smem_raw) + 1023u) & ~1023u;
    unsigned char* sptr = smem_raw + (sbase - smem_u32(smem_raw));
    const int tid = threadIdx.x, warp = tid >> 5, lane = tid & 31;
    const int cta = blockIdx.x, grid = gridDim.x;

    const uint32_t barFull = sbase + kOffBar, barEmpty = barFull + kNS * 8;
    const uint32_t barWFull = barEmpty + kNS * 8, barWEmpty = barWFull + 8, barEp = barWFull + 16;
    const uint32_t barWo = barWFull + 24, barWd = barWFull + 32, barQ = barWFull + 40;
    volatile int* meta = reinterpret_cast<volatile int*>(sptr + kOffMeta);
    volatile int* sProg = reinterpret_cast<volatile int*>(sptr + kOffMisc);
    volatile uint32_t* sEpoch = reinterpret_cast<volatile uint32_t*>(sptr + kOffMisc + 4);
    volatile uint32_t* sWd = reinterpret_cast<volatile uint32_t*>(sptr + kOffMisc + 8);

    int f2, fstep;
    ffn_units(cta, grid, f2, fstep);
    const bool owner = cta < kNOwner;

    if (tid == 256) {
        asm volatile("prefetch.tensormap [%0];" ::"l"(&tmQ) : "memory");
        asm volatile("prefetch.tensormap [%0];" ::"l"(&tmG) : "memory");
        for (int s = 0; s < kNS; s++) { mbar_init(barFull + s * 8, 1); mbar_init(barEmpty + s * 8, 4); }
        mbar_init(barWFull, 1); mbar_init(barWEmpty, 4); mbar_init(barEp, 1); mbar_init(barWo, 1); mbar_init(barWd, 1);
        for (int b = 0; b < kB; b++) mbar_init(barQ + b * 8, 128);
        *sProg = 0;
        asm volatile("fence.mbarrier_init.release.cluster;" ::: "memory");
    }
    if (warp == 8) { __syncwarp(); asm volatile("bar.arrive 0, %0;" ::"n"(kThreads) : "memory"); }
    else asm volatile("bar.sync 0, %0;" ::"n"(kThreads) : "memory");

    if (warp == 8) {
        if (lane == 0) {
            uint64_t pol;
            asm volatile("createpolicy.fractional.L2::evict_first.b64 %0, 1.0;" : "=l"(pol));
            uint64_t polb;
            asm volatile("createpolicy.fractional.L2::evict_normal.b64 %0, 1.0;" : "=l"(polb));
            int slot = 0; uint32_t ph = 1;
            auto next_slot = [&]() { if (++slot == kNS) { slot = 0; ph ^= 1; } };
            auto acquire = [&](int lag) {
                mbar_wait(barEmpty + slot * 8, ph);
                int ls = slot - lag; uint32_t lp = ph ^ 1u;
                if (ls < 0) { ls += kNS; lp ^= 1u; }
                mbar_wait(barFull + ls * 8, lp);
            };
            auto box3 = [&](const CUtensorMap* tm, int col0) {
#pragma unroll 1
                for (int j = 0; j < 3; j++) {
                    acquire(kInflBox);
                    mbar_expect_tx(barFull + slot * 8, kBoxBytes);
                    tma_2d(sbase + kOffRing + slot * kSlotBytes, tm, col0, j * kBoxRows, barFull + slot * 8, polb);
                    next_slot();
                }
            };
            if (owner) box3(&tmQ, cta * 32);
            unsigned raw = atomicAdd(&g_ticket, 1u);
            asm volatile("prefetch.tensormap [%0];" ::"l"(&tmU) : "memory");
            asm volatile("prefetch.tensormap [%0];" ::"l"(&tmK) : "memory");
            asm volatile("prefetch.tensormap [%0];" ::"l"(&tmV) : "memory");
            asm volatile("prefetch.tensormap [%0];" ::"l"(&tmD) : "memory");
            asm volatile("prefetch.tensormap [%0];" ::"l"(&tmO) : "memory");
            if (owner) { box3(&tmG, cta * 32); box3(&tmU, cta * 32); }
            uint32_t wph = 1;
#pragma unroll 1
            for (int f = f2; f < kNFfn; f += fstep) {
                box3(&tmG, f * 32); box3(&tmU, f * 32);
                mbar_wait(barWEmpty, wph); wph ^= 1;
                mbar_expect_tx(barWFull, kWBytes);
                tma_3d(sbase + kOffW, &tmD, 0, 0, f * 32, barWFull, pol);
            }
            mbar_wait(barEp, 0);
            const unsigned tbase = *sEpoch * (unsigned)(kNUnits + grid);
            for (;;) {
                const unsigned u = raw - tbase;
                if (u >= (unsigned)kNUnits) break;
                *sProg = (int)u + 1;
                raw = atomicAdd(&g_ticket, 1u);
                acquire(kInfl);
                meta[slot] = (int)u;
                mbar_expect_tx(barFull + slot * 8, kSlotBytes);
                tma_3d(sbase + kOffRing + slot * kSlotBytes, &tmK, 0, (int)u * kUnitKeys, 0, barFull + slot * 8, pol);
                next_slot();
                acquire(kInfl);
                mbar_expect_tx(barFull + slot * 8, kSlotBytes);
                tma_3d(sbase + kOffRing + slot * kSlotBytes, &tmV, 0, (int)u * kUnitKeys, 0, barFull + slot * 8, pol);
                next_slot();
            }
            *sProg = 0x7fffffff;
            mbar_wait(barEmpty + slot * 8, ph);
            meta[slot] = -1;
            mbar_arrive(barFull + slot * 8);
            if (owner) {
                int ws = slot - 1; uint32_t wp = ph ^ 1u;
                if (ws < 0) { ws += kNS; wp ^= 1u; }
                next_slot();
                while (slot + 3 > kNS) next_slot();
                const uint32_t dst = sbase + kOffRing + slot * kSlotBytes;
                for (int j = 0; j < 3; j++) { mbar_wait(barEmpty + slot * 8, ph); next_slot(); }
                mbar_wait(barFull + ws * 8, wp);
                *sWd = dst;
                mbar_expect_tx(barWd, kWBytes);
                tma_3d(dst, &tmD, 0, 0, cta * 32, barWd, pol);
                mbar_wait(barWd, 0);
                mbar_wait(barWEmpty, wph);
                mbar_expect_tx(barWo, kWBytes);
                tma_3d(sbase + kOffW, &tmO, 0, 0, cta * 32, barWo, pol);
            }
        }
    } else if (warp < 4) {
        const int w = warp, g = lane >> 2, t = lane & 3, mi = lane >> 3, r8 = lane & 7;
        {
            const uint32_t* xr = reinterpret_cast<const uint32_t*>(x + w * kD);
            float v[18];
#pragma unroll
            for (int i = 0; i < 9; i++) {
                uint32_t u = __ldg(xr + lane + 32 * i);
                v[2 * i] = __uint_as_float(u << 16); v[2 * i + 1] = __uint_as_float(u & 0xffff0000u);
            }
            float s = 0.f;
#pragma unroll
            for (int i = 0; i < 18; i++) s += v[i];
#pragma unroll
            for (int o = 16; o; o >>= 1) s += __shfl_xor_sync(0xffffffffu, s, o);
            const float mean = s * (1.f / kD);
            float q = 0.f;
#pragma unroll
            for (int i = 0; i < 18; i++) { float d = v[i] - mean; q += d * d; }
#pragma unroll
            for (int o = 16; o; o >>= 1) q += __shfl_xor_sync(0xffffffffu, q, o);
            const float mb = bf16r(mean), vb = bf16r(q * (1.f / kD));
            const float den = bf16r(sqrtf(bf16r(vb + 1e-5f)));
            uint32_t* xs = reinterpret_cast<uint32_t*>(sptr + kOffXn + w * kXRow);
#pragma unroll
            for (int i = 0; i < 9; i++)
                xs[lane + 32 * i] = pack_bf16(bf16r(v[2 * i] - mb) / den, bf16r(v[2 * i + 1] - mb) / den);
        }
        bar_sync(1, 128);

        int slot = 0; uint32_t ph = 0;
        auto next_slot = [&]() { if (++slot == kNS) { slot = 0; ph ^= 1; } };
        auto gemv3 = [&](float& o0, float& o1) {
            float c0[4] = {0.f, 0.f, 0.f, 0.f}, c1[4] = {0.f, 0.f, 0.f, 0.f};
            const uint32_t xa = sbase + kOffXn + g * kXRow + t * 4;
#pragma unroll 1
            for (int j = 0; j < 3; j++) {
                mbar_wait(barFull + slot * 8, ph);
                const uint32_t sb = sbase + kOffRing + slot * kSlotBytes;
#pragma unroll
                for (int kk = 0; kk < 6; kk++) {
                    const int row = kk * 32 + lane;
                    uint32_t b[4];
                    ldsm_x4_t(sb + row * 64 + ((w ^ ((row >> 1) & 3)) << 4), b);
                    uint32_t a0 = 0, a1 = 0, a2 = 0, a3 = 0;
                    if (g < 4) {
                        const uint32_t ka = xa + (j * kBoxRows + kk * 32) * 2;
                        a0 = lds32(ka); a1 = lds32(ka + 16); a2 = lds32(ka + 32); a3 = lds32(ka + 48);
                    }
                    mma16816(c0, a0, 0u, a1, 0u, b[0], b[1]);
                    mma16816(c1, a2, 0u, a3, 0u, b[2], b[3]);
                }
                __syncwarp();
                if (lane == 0) mbar_arrive(barEmpty + slot * 8);
                next_slot();
            }
            o0 = c0[0] + c1[0]; o1 = c0[1] + c1[1];
        };
        uint32_t tag = 0, wph = 0;
        int f = owner ? -1 : f2;
#pragma unroll 1
        for (;;) {
            float a0, a1;
            gemv3(a0, a1);
            if (f < 0) {
                mbar_wait(barEp, 0);
                tag = (*sEpoch + 1u) & 1u;
                const uint32_t pk = pack_bf16(a0, a1);
                if (g < 4) sts64(sbase + kOffQS + ((g * 4 + t) * 4 + w) * 8, (pk << 16) | tag, (pk & 0xffff0000u) | tag);
                bar_sync(1, 128);
                if (w == 0) {
                    const uint4 v = lds128(sbase + kOffQS + lane * 16);
                    st_relaxed_v4(g_q + ((lane >> 3) * kNOwner + cta) * 32 + (lane & 7) * 4, v.x, v.y, v.z, v.w);
                    __syncwarp();
                    if (lane == 0) {
                        asm volatile("red.relaxed.gpu.global.add.u64 [%0], %1;" ::"l"(&g_qcount), "l"(1ull) : "memory");
                    }
                }
                f = cta;
                continue;
            }
            float u0, u1;
            gemv3(u0, u1);
            const bool own = owner && f == cta;
            if (g < 4) {
                a0 = bf16r(a0); a1 = bf16r(a1); u0 = bf16r(u0); u1 = bf16r(u1);
                a0 = a0 > 0.f ? a0 : 0.f * a0; a1 = a1 > 0.f ? a1 : 0.f * a1;
                sts32(sbase + (own ? kOffHA : kOffHB) + g * 80 + w * 16 + t * 4, pack_bf16(a0 * u0, a1 * u1));
            }
            bar_sync(1, 128);
            if (!own) {
                mbar_wait(barEp, 0);
                tag = (*sEpoch + 1u) & 1u;
                mbar_wait(barWFull, wph); wph ^= 1;
                slice_mma(sbase + kOffHB, sbase + kOffW, g_dslot + (size_t)f * kB * kD, w, lane, tag);
                __syncwarp();
                if (lane == 0) mbar_arrive(barWEmpty);
                bar_sync(1, 128);
                f += fstep;
            } else {
                f = f2;
            }
            if (f >= kNFfn) break;
        }

        if (owner) {
            float* d2 = g_dslot + (size_t)cta * kB * kD;
            const uint32_t nt = tag ^ 1u;
            for (int i = tid; i < kB * kD / 4; i += 128) st_relaxed_v4(d2 + i * 4, nt, nt, nt, nt);
            bar_sync(1, 128);
        }
        const float kScale = 0.08838834764831845f, cs = 1.4426950408889634f;
        const int krow = 16 * w + (mi & 1) * 8 + r8;
        const uint32_t koff = krow * 128;
        const int sub = g >> 1;
        const uint32_t hperm = (g & 1) ? 0x3244u : 0x1044u;
        uint32_t buf = 0;
        int qnext = 0;
        for (;;) {
            mbar_wait(barFull + slot * 8, ph);
            const int u = meta[slot];
            if (u < 0) break;
            if (u >= qnext) {
                const int b = u >> 11;
                mbar_wait(barQ + b * 8, 0);
                qnext = (b + 1) << 11;
            }
            const int pair = u >> 7, j = u & 127;
            uint32_t qf[16];
            if (g < 2) {
                const uint32_t qa = sbase + kOffQ + ((pair * 2 + g) * 4 + t) * 64;
#pragma unroll
                for (int i = 0; i < 4; i++) {
                    uint4 v = lds128(qa + i * 16);
                    qf[4 * i] = v.x; qf[4 * i + 1] = v.y; qf[4 * i + 2] = v.z; qf[4 * i + 3] = v.w;
                }
            } else {
#pragma unroll
                for (int i = 0; i < 16; i++) qf[i] = 0u;
            }
            const uint32_t kb = sbase + kOffRing + slot * kSlotBytes + koff;
            float sA[4] = {0.f, 0.f, 0.f, 0.f}, sB[4] = {0.f, 0.f, 0.f, 0.f};
#pragma unroll
            for (int ks = 0; ks < 8; ks++) {
                uint32_t a[4];
                const int chunk = (ks & 3) * 2 + (mi >> 1);
                ldsm_x4(kb + (ks >> 2) * 8192 + ((chunk ^ r8) << 4), a);
                if (ks & 1) mma16816(sB, a[0], a[1], a[2], a[3], qf[2 * ks], qf[2 * ks + 1]);
                else        mma16816(sA, a[0], a[1], a[2], a[3], qf[2 * ks], qf[2 * ks + 1]);
            }
            __syncwarp();
            if (lane == 0) mbar_arrive(barEmpty + slot * 8);
            next_slot();
            const uint32_t sS = sbase + kOffS + buf * 320;
            {
                uint32_t ra = pack_bf16(sA[0] + sB[0], sA[1] + sB[1]), rb = pack_bf16(sA[2] + sB[2], sA[3] + sB[3]);
                ra = pack_bf16(__uint_as_float(ra << 16) * kScale, __uint_as_float(ra & 0xffff0000u) * kScale);
                rb = pack_bf16(__uint_as_float(rb << 16) * kScale, __uint_as_float(rb & 0xffff0000u) * kScale);
                uint32_t m2 = hmax2(ra, rb);
                m2 = hmax2(m2, __shfl_xor_sync(0xffffffffu, m2, 4));
                m2 = hmax2(m2, __shfl_xor_sync(0xffffffffu, m2, 8));
                m2 = hmax2(m2, __shfl_xor_sync(0xffffffffu, m2, 16));
                if (t == 0) { sts32(sS + (16 * w + g) * 4, ra); sts32(sS + (16 * w + g + 8) * 4, rb); }
                if (lane == 0) sts32(sS + 256 + w * 4, m2);
            }
            mbar_wait(barFull + slot * 8, ph);
            bar_sync(1, 128);
            const uint2 w01 = lds64(sS + (16 * sub + 2 * t) * 4), w23 = lds64(sS + (16 * sub + 2 * t + 8) * 4);
            const uint4 mw = lds128(sS + 256);
            const uint32_t vb = sbase + kOffRing + slot * kSlotBytes + (w >> 1) * 8192;
            uint32_t va[4][2][4];
#pragma unroll
            for (int ks = 0; ks < 4; ks++)
#pragma unroll
                for (int mt = 0; mt < 2; mt++) {
                    const int key = 16 * ks + (mi >> 1) * 8 + r8;
                    const int chunk = (w & 1) * 4 + mt * 2 + (mi & 1);
                    ldsm_x4_t(vb + key * 128 + ((chunk ^ r8) << 4), va[ks][mt]);
                }
            const float mx = __uint_as_float(__byte_perm(hmax2(hmax2(mw.x, mw.y), hmax2(mw.z, mw.w)), 0u, hperm));
            const uint32_t mtag = tagf(mx * cs, tag);
            const float mt_ = untag(mtag);
            const float p0 = ex2(fmaf(__uint_as_float(__byte_perm(w01.x, 0u, hperm)), cs, -mt_));
            const float p1 = ex2(fmaf(__uint_as_float(__byte_perm(w01.y, 0u, hperm)), cs, -mt_));
            const float p2 = ex2(fmaf(__uint_as_float(__byte_perm(w23.x, 0u, hperm)), cs, -mt_));
            const float p3 = ex2(fmaf(__uint_as_float(__byte_perm(w23.y, 0u, hperm)), cs, -mt_));
            const uint32_t pk0 = pack_bf16(p0, p1), pk1 = pack_bf16(p2, p3);
            float o[2][4] = {{0.f, 0.f, 0.f, 0.f}, {0.f, 0.f, 0.f, 0.f}};
            float o2[2][4] = {{0.f, 0.f, 0.f, 0.f}, {0.f, 0.f, 0.f, 0.f}};
#pragma unroll
            for (int ks = 0; ks < 2; ks++) {
                const uint32_t b0 = (sub == ks) ? pk0 : 0u, b1 = (sub == ks) ? pk1 : 0u;
                const uint32_t b2 = (sub == ks + 2) ? pk0 : 0u, b3 = (sub == ks + 2) ? pk1 : 0u;
                mma16816(o[0], va[ks][0][0], va[ks][0][1], va[ks][0][2], va[ks][0][3], b0, b1);
                mma16816(o[1], va[ks][1][0], va[ks][1][1], va[ks][1][2], va[ks][1][3], b0, b1);
                mma16816(o2[0], va[ks + 2][0][0], va[ks + 2][0][1], va[ks + 2][0][2], va[ks + 2][0][3], b2, b3);
                mma16816(o2[1], va[ks + 2][1][0], va[ks + 2][1][1], va[ks + 2][1][2], va[ks + 2][1][3], b2, b3);
            }
            float l = (p0 + p1) + (p2 + p3);
            l += __shfl_xor_sync(0xffffffffu, l, 1);
            l += __shfl_xor_sync(0xffffffffu, l, 2);
            l += __shfl_xor_sync(0xffffffffu, l, 8);
            l += __shfl_xor_sync(0xffffffffu, l, 16);
#pragma unroll
            for (int i = 0; i < 4; i++) { o[0][i] += o2[0][i]; o[1][i] += o2[1][i]; }
            __syncwarp();
            if (lane == 0) mbar_arrive(barEmpty + slot * 8);
            next_slot();
            float k4[4];
#pragma unroll
            for (int i = 0; i < 4; i++) {
                const float send = (t & 1) ? o[0][i] : o[1][i];
                const float keep = (t & 1) ? o[1][i] : o[0][i];
                k4[i] = keep + __shfl_xor_sync(0xffffffffu, send, 1);
            }
            float k2[2];
#pragma unroll
            for (int i = 0; i < 2; i++) {
                const float send = (t & 2) ? k4[i] : k4[2 + i];
                const float keep = (t & 2) ? k4[2 + i] : k4[i];
                k2[i] = keep + __shfl_xor_sync(0xffffffffu, send, 2);
            }
            const int dl = 16 * (t & 1) + 8 * (t >> 1) + g;
            float* po = g_part_o + ((size_t)((pair * 2) * 4 + w) * kUnitsPerPair + j) * 32 + dl;
            st_relaxed(po, tagf(k2[0], tag));
            st_relaxed(po + 4 * kUnitsPerPair * 32, tagf(k2[1], tag));
            if (w == 0 && t == 0 && g < 2) {
                const uint32_t lt = tagf(l, tag);
                st_relaxed_v4(g_part_ml + ((size_t)u * 2 + g) * 4, mtag, lt, mtag, lt);
            }
            if (lane == 0)
                asm volatile("red.relaxed.gpu.global.add.u32 [%0], %1;" ::"l"(g_hint + pair * 32), "r"(1u) : "memory");
            buf ^= 1;
        }
        if (owner) {
            mbar_wait(barWd, 0);
            slice_mma(sbase + kOffHA, *sWd, g_dslot + (size_t)cta * kB * kD, w, lane, tag);
        }
    } else {
        const int bt = tid - 128, w = warp - 4;
        unsigned long long target = 0;
        if (bt == 0) {
            const unsigned long long c0 = ld_relaxed_u64(&g_qcount);
            const unsigned long long e = c0 / (unsigned long long)grid;
            *sEpoch = (uint32_t)e;
            mbar_arrive(barEp);
            target = (e + 1) * (unsigned long long)grid;
            if (!owner)
                asm volatile("red.relaxed.gpu.global.add.u64 [%0], %1;" ::"l"(&g_qcount), "l"(1ull) : "memory");
        }
        const bool fin = cta < kNFin;
        const int foff = cta * 32;
        float xval = 0.f;
        if (fin && bt < 32) xval = __bfloat162float(x[(bt & 3) * kD + cta * 8 + (bt >> 2)]);
        mbar_wait(barEp, 0);
        const uint32_t epoch = *sEpoch;
        const uint32_t tag = (epoch + 1u) & 1u;
        const uint32_t sRed = sbase + kOffRed;
        if (bt == 0) {
            uint32_t n = 0;
            while (ld_relaxed_u64(&g_qcount) < target) {
                __nanosleep(40);
                if (++n > kSpinLimit) __trap();
            }
        }
        bar_sync(2, 128);
#pragma unroll 1
        for (int b = 0; b < kB; b++) {
            const uint32_t* src = g_q + b * (kHQ * kDH) + bt * 4;
            uint4 v[8];
#pragma unroll
            for (int i = 0; i < 8; i++) v[i] = make_uint4(0u, 0u, 0u, 0u);
            uint32_t pend = 0xffu, n = 0;
            for (;;) {
                ld8_v4_masked<128 * 16>(v, src, pend);
                pend = 0;
#pragma unroll
                for (int i = 0; i < 8; i++) pend |= bad4(v[i], tag) << i;
                if (!pend) break;
                if (++n > kSpinLimit) __trap();
            }
#pragma unroll
            for (int i = 0; i < 8; i++) {
                const int e = bt + 128 * i;
                const int head = e >> 5, quarter = (e >> 3) & 3, tt = (e >> 1) & 3, wp = e & 1;
                sts64(sbase + kOffQ + (((b * kHQ + head) * 4 + tt) * 16 + quarter * 4 + wp * 2) * 4,
                      __byte_perm(v[i].x, v[i].y, 0x7632), __byte_perm(v[i].z, v[i].w, 0x7632));
            }
            mbar_arrive(barQ + b * 8);
        }
        if (owner) {
            {
                float* d1 = g_sslot + (size_t)cta * kB * kD;
                const uint32_t nt = tag ^ 1u;
                for (int i = bt; i < kB * kD / 4; i += 128) st_relaxed_v4(d1 + i * 4, nt, nt, nt, nt);
            }
            if (fin) finish(foff, 0, tag, sRed + 512, bt, 0.f, 0.f, out);

            const int hkv = cta >> 3, hh = (cta >> 2) & 1, quarter = cta & 3;
            const int r = bt >> 3, c4 = bt & 7;
#pragma unroll 1
            for (int b = 0; b < kB; b++) {
                const int pair = b * kHKV + hkv;
                {
                    uint32_t n = 0;
                    while (*sProg < (pair + 1) * kUnitsPerPair) {
                        __nanosleep(200);
                        if (++n > kSpinLimit) __trap();
                    }
                    const uint32_t want = (epoch + 1u) * (uint32_t)(4 * kUnitsPerPair);
                    if (lane == 0) {
                        while ((int)(ld_relaxed(g_hint + pair * 32) - want) < 0) {
                            if (*sProg != 0x7fffffff) __nanosleep(100);
                            if (++n > kSpinLimit) __trap();
                        }
                    }
                    __syncwarp();
                }
                const float* po = g_part_o + ((size_t)((pair * 2 + hh) * 4 + quarter) * kUnitsPerPair + r) * 32 + c4 * 4;
                const float* pml = g_part_ml + ((size_t)(pair * kUnitsPerPair + lane) * 2 + hh) * 4;
                uint4 v[8]; uint2 ml[4];
#pragma unroll
                for (int i = 0; i < 8; i++) v[i] = make_uint4(0u, 0u, 0u, 0u);
#pragma unroll
                for (int i = 0; i < 4; i++) ml[i] = make_uint2(0u, 0u);
                uint32_t pend = 0xffu, pend2 = 0xfu, n = 0;
                for (;;) {
                    ld4_v2_masked<32 * 8 * 4>(ml, pml, pend2);
                    ld8_v4_masked<16 * 32 * 4>(v, po, pend);
                    pend = 0; pend2 = 0;
#pragma unroll
                    for (int i = 0; i < 4; i++) pend2 |= (((ml[i].x ^ tag) | (ml[i].y ^ tag)) & 1u) << i;
#pragma unroll
                    for (int i = 0; i < 8; i++) pend |= bad4(v[i], tag) << i;
                    if (!(pend | pend2)) break;
                    if (++n > kSpinLimit) __trap();
                }
                __syncwarp();
                float M = fmaxf(fmaxf(untag(ml[0].x), untag(ml[1].x)), fmaxf(untag(ml[2].x), untag(ml[3].x)));
#pragma unroll
                for (int o = 16; o; o >>= 1) M = fmaxf(M, __shfl_xor_sync(0xffffffffu, M, o));
                float wt[4], L = 0.f;
#pragma unroll
                for (int i = 0; i < 4; i++) {
                    wt[i] = ex2(untag(ml[i].x) - M);
                    L = fmaf(wt[i], untag(ml[i].y), L);
                }
#pragma unroll
                for (int o = 16; o; o >>= 1) L += __shfl_xor_sync(0xffffffffu, L, o);
                float a0 = 0.f, a1 = 0.f, a2 = 0.f, a3 = 0.f;
#pragma unroll
                for (int i = 0; i < 8; i++) {
                    const float wi = __shfl_sync(0xffffffffu, wt[i >> 1], r + 16 * (i & 1));
                    a0 = fmaf(wi, untag(v[i].x), a0); a1 = fmaf(wi, untag(v[i].y), a1);
                    a2 = fmaf(wi, untag(v[i].z), a2); a3 = fmaf(wi, untag(v[i].w), a3);
                }
#pragma unroll
                for (int o = 8; o <= 16; o <<= 1) {
                    a0 += __shfl_xor_sync(0xffffffffu, a0, o); a1 += __shfl_xor_sync(0xffffffffu, a1, o);
                    a2 += __shfl_xor_sync(0xffffffffu, a2, o); a3 += __shfl_xor_sync(0xffffffffu, a3, o);
                }
                if (lane < 8) sts128f(sRed + w * 128 + c4 * 16, a0, a1, a2, a3);
                bar_sync(2, 128);
                if (bt < 32) {
                    float o = 0.f;
#pragma unroll
                    for (int wv = 0; wv < 4; wv++) o += __uint_as_float(lds32(sRed + wv * 128 + bt * 4));
                    *reinterpret_cast<__nv_bfloat16*>(sptr + kOffOA + b * 80 + bt * 2) = __float2bfloat16_rn(o / L);
                }
                bar_sync(2, 128);
            }
            mbar_wait(barWo, 0);
            slice_mma(sbase + kOffOA, sbase + kOffW, g_sslot + (size_t)cta * kB * kD, w, lane, tag);
            if (fin) {
                const float gate = finish(foff, 1, tag, sRed + 1024, bt, 0.f, 0.f, out);
                finish(foff, 2, tag, sRed + 512, bt, gate, xval, out);
            }
        }
    }
}

constexpr int kFbSplit = 16, kFbKeys = kSK / kFbSplit;
__device__ float g_fb_q[kB * kHQ * kDH], g_fb_h[kB * kF], g_fb_o[kNPair * kFbSplit * 2 * (kDH + 2)];

__global__ void __launch_bounds__(256) fb_proj(const __nv_bfloat16* x, const __nv_bfloat16* wq, const __nv_bfloat16* wg,
                                               const __nv_bfloat16* wu) {
    __shared__ float xn[kB][kD], red[2][4][kB][64];
    const int tid = threadIdx.x, warp = tid >> 5, lane = tid & 31;
    if (warp < kB) {
        float s = 0.f, q = 0.f;
        for (int i = lane; i < kD; i += 32) s += __bfloat162float(x[warp * kD + i]);
        for (int o = 16; o; o >>= 1) s += __shfl_xor_sync(0xffffffffu, s, o);
        const float mean = s * (1.f / kD);
        for (int i = lane; i < kD; i += 32) { const float d = __bfloat162float(x[warp * kD + i]) - mean; q += d * d; }
        for (int o = 16; o; o >>= 1) q += __shfl_xor_sync(0xffffffffu, q, o);
        const float mb = bf16r(mean), den = bf16r(sqrtf(bf16r(bf16r(q * (1.f / kD)) + 1e-5f)));
        for (int i = lane; i < kD; i += 32) xn[warp][i] = bf16r(bf16r(__bfloat162float(x[warp * kD + i]) - mb) / den);
    }
    __syncthreads();
    const bool isq = blockIdx.x < 64;
    const int col = (isq ? blockIdx.x : blockIdx.x - 64) * 64 + (tid & 63), kq = tid >> 6;
    float a[kB] = {0.f, 0.f, 0.f, 0.f}, u[kB] = {0.f, 0.f, 0.f, 0.f};
    for (int k = kq * 144; k < kq * 144 + 144; k++) {
        const float w0 = __bfloat162float(isq ? wq[(size_t)k * (kHQ * kDH) + col] : wg[(size_t)k * kF + col]);
        const float w1 = isq ? 0.f : __bfloat162float(wu[(size_t)k * kF + col]);
        for (int b = 0; b < kB; b++) { a[b] = fmaf(xn[b][k], w0, a[b]); u[b] = fmaf(xn[b][k], w1, u[b]); }
    }
    for (int b = 0; b < kB; b++) { red[0][kq][b][tid & 63] = a[b]; red[1][kq][b][tid & 63] = u[b]; }
    __syncthreads();
    const int b = kq, c = tid & 63;
    const float ga = bf16r(red[0][0][b][c] + red[0][1][b][c] + red[0][2][b][c] + red[0][3][b][c]);
    const float up = bf16r(red[1][0][b][c] + red[1][1][b][c] + red[1][2][b][c] + red[1][3][b][c]);
    if (isq) g_fb_q[b * (kHQ * kDH) + col] = ga;
    else g_fb_h[b * kF + col] = bf16r((ga > 0.f ? ga : 0.f * ga) * up);
}

__global__ void __launch_bounds__(128) fb_attn(const __nv_bfloat16* kc, const __nv_bfloat16* vc) {
    __shared__ float sc[2][kFbKeys], mx[2][4], sm[2][4];
    const int pair = blockIdx.x / kFbSplit, split = blockIdx.x % kFbSplit;
    const int tid = threadIdx.x, warp = tid >> 5, lane = tid & 31;
    const size_t base = ((size_t)pair * kSK + (size_t)split * kFbKeys) * kDH;
    const float* q = g_fb_q + (pair / kHKV) * (kHQ * kDH) + (pair % kHKV) * 2 * kDH;
    float m0 = -INFINITY, m1 = -INFINITY;
    for (int k = warp; k < kFbKeys; k += 4) {
        float s0 = 0.f, s1 = 0.f;
        for (int d = lane; d < kDH; d += 32) {
            const float kv = __bfloat162float(kc[base + (size_t)k * kDH + d]);
            s0 = fmaf(q[d], kv, s0); s1 = fmaf(q[kDH + d], kv, s1);
        }
        for (int o = 16; o; o >>= 1) { s0 += __shfl_xor_sync(0xffffffffu, s0, o); s1 += __shfl_xor_sync(0xffffffffu, s1, o); }
        s0 = bf16r(bf16r(s0) * 0.08838834764831845f); s1 = bf16r(bf16r(s1) * 0.08838834764831845f);
        if (lane == 0) { sc[0][k] = s0; sc[1][k] = s1; }
        m0 = fmaxf(m0, s0); m1 = fmaxf(m1, s1);
    }
    if (lane == 0) { mx[0][warp] = m0; mx[1][warp] = m1; }
    __syncthreads();
    m0 = fmaxf(fmaxf(mx[0][0], mx[0][1]), fmaxf(mx[0][2], mx[0][3]));
    m1 = fmaxf(fmaxf(mx[1][0], mx[1][1]), fmaxf(mx[1][2], mx[1][3]));
    float l0 = 0.f, l1 = 0.f;
    for (int k = tid; k < kFbKeys; k += 128) {
        const float p0 = __expf(sc[0][k] - m0), p1 = __expf(sc[1][k] - m1);
        l0 += p0; l1 += p1; sc[0][k] = bf16r(p0); sc[1][k] = bf16r(p1);
    }
    for (int o = 16; o; o >>= 1) { l0 += __shfl_xor_sync(0xffffffffu, l0, o); l1 += __shfl_xor_sync(0xffffffffu, l1, o); }
    if (lane == 0) { sm[0][warp] = l0; sm[1][warp] = l1; }
    __syncthreads();
    float o0 = 0.f, o1 = 0.f;
    for (int k = 0; k < kFbKeys; k++) {
        const float v = __bfloat162float(vc[base + (size_t)k * kDH + tid]);
        o0 = fmaf(sc[0][k], v, o0); o1 = fmaf(sc[1][k], v, o1);
    }
    float* dst = g_fb_o + (size_t)blockIdx.x * 2 * (kDH + 2);
    dst[tid] = o0; dst[kDH + 2 + tid] = o1;
    if (tid == 0) {
        dst[kDH] = m0; dst[kDH + 1] = sm[0][0] + sm[0][1] + sm[0][2] + sm[0][3];
        dst[2 * kDH + 2] = m1; dst[2 * kDH + 3] = sm[1][0] + sm[1][1] + sm[1][2] + sm[1][3];
    }
}

__global__ void __launch_bounds__(256) fb_out(const __nv_bfloat16* x, const __nv_bfloat16* wo, const __nv_bfloat16* wd,
                                              __nv_bfloat16* out) {
    __shared__ float o[kHQ * kDH], red[2][4][64];
    const int b = blockIdx.x / 9, tid = threadIdx.x, col = (blockIdx.x % 9) * 64 + (tid & 63), kq = tid >> 6;
    for (int i = tid; i < kHQ * kDH; i += 256) {
        const int head = i / kDH, d = i % kDH;
        const float* src = g_fb_o + ((size_t)(b * kHKV + head / 2) * kFbSplit * 2 + (head & 1)) * (kDH + 2);
        float M = -INFINITY, L = 0.f, acc = 0.f;
        for (int sp = 0; sp < kFbSplit; sp++) M = fmaxf(M, src[sp * 2 * (kDH + 2) + kDH]);
        for (int sp = 0; sp < kFbSplit; sp++) {
            const float* e = src + sp * 2 * (kDH + 2);
            const float w = __expf(e[kDH] - M);
            L = fmaf(w, e[kDH + 1], L); acc = fmaf(w, e[d], acc);
        }
        o[i] = bf16r(acc / L);
    }
    __syncthreads();
    float s = 0.f, dn = 0.f;
    for (int k = kq * 1024; k < kq * 1024 + 1024; k++) s = fmaf(o[k], __bfloat162float(wo[(size_t)k * kD + col]), s);
    for (int f = kq * 1152; f < kq * 1152 + 1152; f++) dn = fmaf(g_fb_h[b * kF + f], __bfloat162float(wd[(size_t)f * kD + col]), dn);
    red[0][kq][tid & 63] = s; red[1][kq][tid & 63] = dn;
    __syncthreads();
    if (tid < 64) {
        s = bf16r(red[0][0][tid] + red[0][1][tid] + red[0][2][tid] + red[0][3][tid]);
        dn = bf16r(red[1][0][tid] + red[1][1][tid] + red[1][2][tid] + red[1][3][tid]);
        const float gate = bf16r(dn / (1.f + __expf(-dn)));
        out[b * kD + col] = __float2bfloat16_rn(__bfloat162float(x[b * kD + col]) + bf16r(s * gate));
    }
}

typedef CUresult (*EncodeFn)(CUtensorMap*, CUtensorMapDataType, cuuint32_t, void*, const cuuint64_t*,
                             const cuuint64_t*, const cuuint32_t*, const cuuint32_t*, CUtensorMapInterleave,
                             CUtensorMapSwizzle, CUtensorMapL2promotion, CUtensorMapFloatOOBfill);

struct HostState {
    bool init, ok;
    int grid;
    const void* ptr[7];
    CUtensorMap tm[7];
};
HostState g_host;

}

extern "C" void kernel_launch(void* const* d_in, const int* in_sizes, int n_in, void* d_out, int out_size) {
    (void)in_sizes; (void)n_in; (void)out_size;
    HostState& hs = g_host;
    const void* ptrs[7] = {d_in[1], d_in[2], d_in[3], d_in[6], d_in[7], d_in[8], d_in[4]};
    bool need = !hs.init;
    for (int i = 0; i < 7 && !need; i++) need = hs.ptr[i] != ptrs[i];
    if (need) {
        EncodeFn enc = nullptr;
        cudaDriverEntryPointQueryResult qr;
        cudaGetDriverEntryPoint("cuTensorMapEncodeTiled", (void**)&enc, cudaEnableDefault, &qr);
        int bad = enc ? 0 : 1;
        const cuuint32_t es[3] = {1, 1, 1};
        for (int i = 0; i < 2; i++) {
            const cuuint64_t gd[3] = {64, (cuuint64_t)kNPair * kSK, 2};
            const cuuint64_t gs[2] = {256, 128};
            const cuuint32_t bx[3] = {64, kUnitKeys, 2};
            if (enc) bad |= (int)enc(&hs.tm[i], CU_TENSOR_MAP_DATA_TYPE_BFLOAT16, 3, (void*)ptrs[i], gd, gs, bx, es,
                CU_TENSOR_MAP_INTERLEAVE_NONE, CU_TENSOR_MAP_SWIZZLE_128B, CU_TENSOR_MAP_L2_PROMOTION_L2_128B,
                CU_TENSOR_MAP_FLOAT_OOB_FILL_NONE);
        }
        for (int i = 2; i < 5; i++) {
            const cuuint64_t ncol = (i == 2) ? (cuuint64_t)kHQ * kDH : (cuuint64_t)kF;
            const cuuint64_t gd[2] = {ncol, (cuuint64_t)kD};
            const cuuint64_t gs[1] = {ncol * 2};
            const cuuint32_t bx[2] = {32, kBoxRows};
            if (enc) bad |= (int)enc(&hs.tm[i], CU_TENSOR_MAP_DATA_TYPE_BFLOAT16, 2, (void*)ptrs[i], gd, gs, bx, es,
                CU_TENSOR_MAP_INTERLEAVE_NONE, CU_TENSOR_MAP_SWIZZLE_64B, CU_TENSOR_MAP_L2_PROMOTION_L2_128B,
                CU_TENSOR_MAP_FLOAT_OOB_FILL_NONE);
        }
        for (int i = 5; i < 7; i++) {
            const cuuint64_t gd[3] = {64, 9, (i == 5) ? (cuuint64_t)kF : (cuuint64_t)kHQ * kDH};
            const cuuint64_t gs[2] = {128, (cuuint64_t)kD * 2};
            const cuuint32_t bx[3] = {64, 9, 32};
            if (enc) bad |= (int)enc(&hs.tm[i], CU_TENSOR_MAP_DATA_TYPE_BFLOAT16, 3, (void*)ptrs[i], gd, gs, bx, es,
                CU_TENSOR_MAP_INTERLEAVE_NONE, CU_TENSOR_MAP_SWIZZLE_128B, CU_TENSOR_MAP_L2_PROMOTION_L2_128B,
                CU_TENSOR_MAP_FLOAT_OOB_FILL_NONE);
        }
        for (int i = 0; i < 7; i++) hs.ptr[i] = ptrs[i];
        if (!hs.init) {
            int dev = 0, sms = 0;
            cudaGetDevice(&dev);
            cudaDeviceGetAttribute(&sms, cudaDevAttrMultiProcessorCount, dev);
            if (cudaFuncSetAttribute(fused_decode_kernel, cudaFuncAttributeMaxDynamicSharedMemorySize, kSmemBytes) != cudaSuccess) {
                (void)cudaGetLastError();
                sms = 0;
            }
            hs.grid = sms > kMaxGrid ? kMaxGrid : sms;
            hs.init = true;
        }
        hs.ok = !bad && hs.grid >= kNOwner;
    }
    if (!hs.ok) {
        typedef const __nv_bfloat16* P;
        fb_proj<<<64 + kF / 64, 256, 0, cudaStreamPerThread>>>((P)d_in[0], (P)d_in[3], (P)d_in[6], (P)d_in[7]);
        fb_attn<<<kNPair * kFbSplit, 128, 0, cudaStreamPerThread>>>((P)d_in[1], (P)d_in[2]);
        fb_out<<<kB * 9, 256, 0, cudaStreamPerThread>>>((P)d_in[0], (P)d_in[4], (P)d_in[8], (__nv_bfloat16*)d_out);
        return;
    }
    fused_decode_kernel<<<hs.grid, kThreads, kSmemBytes, cudaStreamPerThread>>>(
        hs.tm[0], hs.tm[1], hs.tm[2], hs.tm[3], hs.tm[4], hs.tm[5], hs.tm[6],
        (const __nv_bfloat16*)d_in[0], (__nv_bfloat16*)d_out);
}
```
